```python
import torch

def _softmax(x, axis=-1):
    return torch.softmax(x, dim=axis)

def _gelu(x):
    return torch.nn.functional.gelu(x, approximate='tanh')

def _silu(x):
    return torch.nn.functional.silu(x)

def _sigmoid(x):
    return torch.sigmoid(x)

def _layernorm(x, axis=-1, eps=1e-05):
    m = x.mean(dim=axis, keepdim=True)
    v = x.var(dim=axis, keepdim=True, unbiased=False)
    return (x - m) / torch.sqrt(v + eps)

def _scatter_add(tgt, idx, src, axis=0):
    return tgt.clone().index_add_(axis, idx, src)

def _segment_sum(src, seg, n):
    out = torch.zeros((n,) + src.shape[1:], dtype=src.dtype)
    return out.index_add_(0, seg, src)

def _pad(x, pw):
    flat = tuple((v for pair in reversed(pw) for v in pair))
    return torch.nn.functional.pad(x, flat)
kernel_name = 'adaLN_cond__gqa_block_cached__geglu_ffn__decode'

def setup_inputs():

    _w = lambda a: (lambda t: t.to(torch.bfloat16) if t.is_floating_point() else t)(torch.as_tensor(a))

    def _A_setup():
        B, Sq, D = (8, 1, 576)
        Hq, Hkv, Sk, Dh = (32, 16, 8192, 128)
        assert Hq % Hkv == 0, (Hq, Hkv)
        return {'x': _w((lambda *s: torch.randn(*s, dtype=torch.bfloat16) * 0.1)(B, Sq, D)), 'k_cache': _w((lambda *s: torch.randn(*s, dtype=torch.bfloat16) * 0.8)(B, Hkv, Sk, Dh)), 'v_cache': _w((lambda *s: torch.randn(*s, dtype=torch.bfloat16) * 0.8)(B, Hkv, Sk, Dh)), 'wq': _w((lambda *s: torch.randn(*s, dtype=torch.bfloat16) * 0.8)(D, Hq * Dh) * D ** (-0.5)), 'wo': _w((lambda *s: torch.randn(*s, dtype=torch.bfloat16) * 0.8)(Hq * Dh, D) * (Hq * Dh) ** (-0.5))}
    _A_in = _A_setup()

    def _B_setup():
        B, S, D, F = (8, 1, 576, 4608)
        return {'x': _w((lambda *s: torch.randn(*s, dtype=torch.bfloat16) * 0.1)(B, S, D)), 'w_gate': _w((lambda *s: torch.randn(*s, dtype=torch.bfloat16) * 0.1)(D, F)), 'w_up': _w((lambda *s: torch.randn(*s, dtype=torch.bfloat16) * 0.1)(D, F)), 'w_down': _w((lambda *s: torch.randn(*s, dtype=torch.bfloat16) * 0.1)(F, D))}
    _B_in = _B_setup()
    return {'A_x': _A_in['x'], 'A_k_cache': _A_in['k_cache'], 'A_v_cache': _A_in['v_cache'], 'A_wq': _A_in['wq'], 'A_wo': _A_in['wo'], 'B_x': _B_in['x'], 'B_w_gate': _B_in['w_gate'], 'B_w_up': _B_in['w_up'], 'B_w_down': _B_in['w_down'], 'c': _w((lambda *s: torch.randn(*s, dtype=torch.bfloat16) * 0.4)(8, 576) * 8.0), 'w_mod': _w((lambda *s: torch.randn(*s, dtype=torch.bfloat16) * 0.4)(576, 6 * 576) * 576 ** (-0.5) * 8.0)}

def reference(A_x, A_k_cache, A_v_cache, A_wq, A_wo, B_x, B_w_gate, B_w_up, B_w_down, c, w_mod):

    def _A_ref(x, k_cache, v_cache, wq, wo):
        B, Sq, D = x.shape
        Hq, Dh = (32, 128)
        Hkv = k_cache.shape[1]
        rep = Hq // Hkv
        q = (lambda x, *d: x.permute(*d))((x @ wq).reshape(B, Sq, Hq, Dh), 0, 2, 1, 3)
        k = (lambda x, n, axis: torch.repeat_interleave(x, n, dim=axis))(k_cache, rep, axis=1)
        v = (lambda x, n, axis: torch.repeat_interleave(x, n, dim=axis))(v_cache, rep, axis=1)
        scores = torch.einsum('bhqd,bhkd->bhqk', q, k) * Dh ** (-0.5)
        p = _softmax(scores, axis=-1)
        o = torch.einsum('bhqk,bhkd->bhqd', p, v)
        return (lambda x, *d: x.permute(*d))(o, 0, 2, 1, 3).reshape(B, Sq, Hq * Dh) @ wo

    def _B_ref(x, w_gate, w_up, w_down):
        return _gelu(x @ w_gate) * (x @ w_up) @ w_down
    x = A_x
    mod = (_silu(c) @ w_mod).reshape(c.shape[0], 6, 1, -1)
    sa, ca, ga, sb, cb, gb = (mod[:, 0].clone(), mod[:, 1].clone(), mod[:, 2].clone(), mod[:, 3].clone(), mod[:, 4].clone(), mod[:, 5].clone())
    h = _layernorm(x, axis=-1) * (1 + ca) + sa
    x = x + ga * _A_ref(h, A_k_cache, A_v_cache, A_wq, A_wo)
    h = _layernorm(x, axis=-1) * (1 + cb) + sb
    x = x + gb * _B_ref(h, B_w_gate, B_w_up, B_w_down)
    return x
```

```cpp
#include <cuda_runtime.h>
#include <cuda_bf16.h>
#include <cuda.h>
#include <stdint.h>

namespace {

constexpr int NB = 8;
constexpr int DM = 576;
constexpr int HKV = 16;
constexpr int SK = 8192;
constexpr int DH = 128;
constexpr int FF = 4608;
constexpr int NPAIR = NB * HKV;
constexpr int UKEYS = 128;
constexpr int UNITS = SK / UKEYS;
constexpr int SLOT = 32768;
constexpr int NSLOT = 6;
constexpr int NROLE = 128;
constexpr int MAXCTA = 132;
constexpr int MAXS = MAXCTA + 1;
constexpr int PSTRIDE = 264;
constexpr int NCONS = 256;
constexpr int NTHREADS = 288;

constexpr int SM_SCR = 0;
constexpr int SM_RING = 8192;
constexpr int SM_BUFA = SM_RING + NSLOT * SLOT;
constexpr int BUFA_PITCH = 584;
constexpr int SM_RED = SM_BUFA + 8 * BUFA_PITCH * 2;
constexpr int SM_ACT = SM_RED + 4096;
constexpr int ACT_PITCH = 56;
constexpr int SM_ML = SM_ACT + 8 * ACT_PITCH * 2;
constexpr int SM_STAT = SM_ML + 128;
constexpr int SM_META = SM_STAT + 64;
constexpr int SM_BAR = SM_META + 32;
constexpr int SM_EPOCH = SM_BAR + 16 * 8;
constexpr int SM_TOTAL = SM_EPOCH + 16;
constexpr int SMEM_BYTES = SM_TOTAL + 1024;
constexpr int BUFO_PITCH = 264;

struct __align__(16) Ctr { unsigned joined, done, next, pad; };

__device__ Ctr g_ctr[2][NPAIR];
__device__ unsigned g_epoch;
__device__ unsigned g_started[2];
__device__ __align__(16) unsigned g_h[NB * DM];
__device__ __align__(16) unsigned g_mod[NB * 6 * DM];
__device__ __align__(16) unsigned g_q[NB * 4096];
__device__ __align__(16) float g_part[(size_t)NPAIR * MAXS * PSTRIDE];
__device__ __align__(16) unsigned g_wop[HKV * DM * NB];
__device__ __align__(16) unsigned g_x2[NB * DM];
__device__ __align__(16) unsigned g_dnp[(size_t)NROLE * DM * NB];

struct Params {
    const __nv_bfloat16* x;
    const __nv_bfloat16* c;
    __nv_bfloat16* out;
};

#define TRAP_AT(line) __trap()

__device__ __forceinline__ uint32_t smem_u32(const void* p) { return (uint32_t)__cvta_generic_to_shared(p); }
__device__ __forceinline__ void mbar_init(uint32_t bar, uint32_t cnt) {
    asm volatile("mbarrier.init.shared::cta.b64 [%0], %1;" ::"r"(bar), "r"(cnt) : "memory");
}
__device__ __forceinline__ void mbar_expect_tx(uint32_t bar, uint32_t bytes) {
    asm volatile("mbarrier.arrive.expect_tx.shared::cta.b64 _, [%0], %1;" ::"r"(bar), "r"(bytes) : "memory");
}
__device__ __forceinline__ void mbar_arrive(uint32_t bar) {
    asm volatile("mbarrier.arrive.shared::cta.b64 _, [%0];" ::"r"(bar) : "memory");
}
__device__ __forceinline__ bool mbar_try(uint32_t bar, uint32_t parity) {
    uint32_t ok;
    asm volatile(
        "{\n.reg .pred p;\n"
        "mbarrier.try_wait.parity.shared::cta.b64 p, [%1], %2;\n"
        "selp.u32 %0, 1, 0, p;\n}\n"
        : "=r"(ok) : "r"(bar), "r"(parity) : "memory");
    return ok != 0;
}
__device__ __forceinline__ void mbar_wait(uint32_t bar, uint32_t parity) {
    unsigned spins = 0;
    while (!mbar_try(bar, parity)) {
        if (++spins > (1u << 26)) TRAP_AT(__LINE__);
    }
}
__device__ __forceinline__ void tma2d(uint32_t dst, const CUtensorMap* map, int c0, int c1, uint32_t bar) {
    asm volatile(
        "cp.async.bulk.tensor.2d.shared::cluster.global.mbarrier::complete_tx::bytes [%0], [%1, {%3, %4}], [%2];"
        ::"r"(dst), "l"((uint64_t)map), "r"(bar), "r"(c0), "r"(c1) : "memory");
}
__device__ __forceinline__ void ldsm4(uint32_t addr, uint32_t (&r)[4]) {
    asm volatile("ldmatrix.sync.aligned.m8n8.x4.shared.b16 {%0,%1,%2,%3}, [%4];"
                 : "=r"(r[0]), "=r"(r[1]), "=r"(r[2]), "=r"(r[3]) : "r"(addr) : "memory");
}
__device__ __forceinline__ void ldsm4t(uint32_t addr, uint32_t (&r)[4]) {
    asm volatile("ldmatrix.sync.aligned.m8n8.x4.trans.shared.b16 {%0,%1,%2,%3}, [%4];"
                 : "=r"(r[0]), "=r"(r[1]), "=r"(r[2]), "=r"(r[3]) : "r"(addr) : "memory");
}
__device__ __forceinline__ void mma16816(float (&c)[4], const uint32_t (&a)[4], uint32_t b0, uint32_t b1) {
    asm volatile(
        "mma.sync.aligned.m16n8k16.row.col.f32.bf16.bf16.f32 {%0,%1,%2,%3}, {%4,%5,%6,%7}, {%8,%9}, {%0,%1,%2,%3};"
        : "+f"(c[0]), "+f"(c[1]), "+f"(c[2]), "+f"(c[3])
        : "r"(a[0]), "r"(a[1]), "r"(a[2]), "r"(a[3]), "r"(b0), "r"(b1));
}
__device__ __forceinline__ void cons_sync() { asm volatile("bar.sync 1, 256;" ::: "memory"); }
__device__ __forceinline__ uint32_t lds32(uint32_t addr) {
    uint32_t v; asm volatile("ld.shared.u32 %0, [%1];" : "=r"(v) : "r"(addr) : "memory"); return v;
}
__device__ __forceinline__ uint2 ldg_relaxed2(const unsigned* p) {
    uint2 v; asm volatile("ld.relaxed.gpu.global.v2.u32 {%0,%1}, [%2];" : "=r"(v.x), "=r"(v.y) : "l"(p) : "memory"); return v;
}
__device__ __forceinline__ uint4 ldg_relaxed4(const unsigned* p) {
    uint4 v; asm volatile("ld.relaxed.gpu.global.v4.u32 {%0,%1,%2,%3}, [%4];"
                          : "=r"(v.x), "=r"(v.y), "=r"(v.z), "=r"(v.w) : "l"(p) : "memory"); return v;
}
__device__ __forceinline__ unsigned ldg_relaxed1(const unsigned* p) {
    unsigned v; asm volatile("ld.relaxed.gpu.global.u32 %0, [%1];" : "=r"(v) : "l"(p) : "memory"); return v;
}
__device__ __forceinline__ void stg_relaxed1(unsigned* p, unsigned v) {
    asm volatile("st.relaxed.gpu.global.u32 [%0], %1;" ::"l"(p), "r"(v) : "memory");
}
__device__ __forceinline__ void stg_relaxed2(unsigned* p, unsigned a, unsigned b) {
    asm volatile("st.relaxed.gpu.global.v2.u32 [%0], {%1,%2};" ::"l"(p), "r"(a), "r"(b) : "memory");
}
__device__ __forceinline__ float ex2(float x) { float y; asm("ex2.approx.ftz.f32 %0, %1;" : "=f"(y) : "f"(x)); return y; }

__device__ __forceinline__ float bfr(float x) { return __bfloat162float(__float2bfloat16_rn(x)); }
__device__ __forceinline__ unsigned bf_bits(float x) { return (unsigned)__bfloat16_as_ushort(__float2bfloat16_rn(x)); }
__device__ __forceinline__ float bf_hi(unsigned w) { return __uint_as_float(w & 0xffff0000u); }
__device__ __forceinline__ float bf_lo(unsigned w) { return __uint_as_float(w << 16); }
__device__ __forceinline__ unsigned pack_hi(unsigned lo_word, unsigned hi_word) {
    return __byte_perm(lo_word, hi_word, 0x7632);
}
__device__ __forceinline__ unsigned pack_bf2(float lo, float hi) {
    unsigned r; asm("cvt.rn.bf16x2.f32 %0, %1, %2;" : "=r"(r) : "f"(hi), "f"(lo)); return r;
}
constexpr float LOG2E = 1.4426950408889634f;
constexpr float QSCALE = 0.08838834764831845f;
constexpr unsigned SPIN_LIMIT = 1u << 24;

template <int N>
__device__ __forceinline__ void poll_row16(const unsigned* base, int lane, unsigned tag16, uint2 (&v)[N]) {
    unsigned spins = 0;
    while (true) {
        v[0] = ldg_relaxed2(base + 2 * lane);
        if ((v[0].x & 0xffffu) == tag16 && (v[0].y & 0xffffu) == tag16) break;
        if (++spins > SPIN_LIMIT) TRAP_AT(__LINE__);
        __nanosleep(64);
    }
    bool ok;
    spins = 0;
#pragma unroll
    for (int i = 1; i < N; i++) v[i] = ldg_relaxed2(base + 2 * (lane + 32 * i));
    while (true) {
        ok = true;
#pragma unroll
        for (int i = 1; i < N; i++) {
            if ((v[i].x & 0xffffu) != tag16 || (v[i].y & 0xffffu) != tag16) {
                v[i] = ldg_relaxed2(base + 2 * (lane + 32 * i));
                ok = false;
            }
        }
        if (ok) break;
        if (++spins > SPIN_LIMIT) TRAP_AT(__LINE__);
    }
}

__device__ __forceinline__ void ln_stats(const float (&x)[18], float& mean_r, float& sd_r) {
    float s = 0.f;
#pragma unroll
    for (int i = 0; i < 18; i++) s += x[i];
#pragma unroll
    for (int o = 16; o; o >>= 1) s += __shfl_xor_sync(0xffffffffu, s, o);
    const float mean = s * (1.0f / 576.0f);
    float q = 0.f;
#pragma unroll
    for (int i = 0; i < 18; i++) { float d = x[i] - mean; q += d * d; }
#pragma unroll
    for (int o = 16; o; o >>= 1) q += __shfl_xor_sync(0xffffffffu, q, o);
    const float var = bfr(q * (1.0f / 576.0f));
    mean_r = bfr(mean);
    sd_r = bfr(sqrtf(bfr(var + 1e-5f)));
}
__device__ __forceinline__ float ln_mod(float x, float mean_r, float sd_r, float cmul, float sadd) {
    float y = bfr(bfr(x - mean_r) / sd_r);
    y = bfr(y * bfr(1.0f + cmul));
    return bfr(y + sadd);
}

__global__ void __launch_bounds__(NTHREADS, 1)
fused_kernel(const __grid_constant__ CUtensorMap tmK, const __grid_constant__ CUtensorMap tmV,
             const __grid_constant__ CUtensorMap tmMod, const __grid_constant__ CUtensorMap tmQ,
             const __grid_constant__ CUtensorMap tmO, const __grid_constant__ CUtensorMap tmG,
             const __grid_constant__ CUtensorMap tmU, const __grid_constant__ CUtensorMap tmD,
             const Params prm) {
    extern __shared__ unsigned char smem_raw[];
    const uint32_t sb = (smem_u32(smem_raw) + 1023u) & ~1023u;
    unsigned char* sp = smem_raw + (sb - smem_u32(smem_raw));
    const int tid = threadIdx.x, warp = tid >> 5, lane = tid & 31;
    const int cta = blockIdx.x;
    const uint32_t bar_full = sb + SM_BAR, bar_empty = sb + SM_BAR + 48, bar_ctrl = sb + SM_BAR + 96;
    volatile int2* meta = reinterpret_cast<volatile int2*>(sp + SM_META);
    volatile unsigned* s_epoch = reinterpret_cast<volatile unsigned*>(sp + SM_EPOCH);

    if (warp == 8) {
        if (lane == 0) {
            for (int i = 0; i < NSLOT; i++) { mbar_init(bar_full + 8 * i, 1); mbar_init(bar_empty + 8 * i, 8); }
            for (int i = 0; i < 3; i++) mbar_init(bar_ctrl + 8 * i, 1);
            asm volatile("fence.mbarrier_init.release.cluster;" ::: "memory");
            asm volatile("fence.proxy.async.shared::cta;" ::: "memory");
            if (cta < 108) {
                mbar_expect_tx(bar_full + 0, 36864);
                const int cA = cta < 36 ? 16 * cta : 1152 + 32 * (cta - 36);
                const int cB = cta < 36 ? 576 + 16 * cta : cA + 16;
                for (int i = 0; i < 3; i++) {
                    tma2d(sb + i * 6144, &tmMod, cA, 192 * i, bar_full + 0);
                    tma2d(sb + 18432 + i * 6144, &tmMod, cB, 192 * i, bar_full + 0);
                }
            } else {
                mbar_arrive(bar_full + 0);
            }
            if (cta < NROLE) {
                mbar_expect_tx(bar_full + 8, 36864);
                for (int i = 0; i < 3; i++) tma2d(sb + 36864 + i * 12288, &tmQ, 32 * cta, 192 * i, bar_full + 8);
                for (int u = 0; u < 2; u++) {
                    const int s = 2 + 2 * u;
                    const int row = (cta * SK + u * UKEYS) * 2;
                    mbar_expect_tx(bar_full + 8 * s, SLOT);
                    tma2d(sb + SM_RING + s * SLOT, &tmK, 0, row, bar_full + 8 * s);
                    mbar_expect_tx(bar_full + 8 * (s + 1), SLOT);
                    tma2d(sb + SM_RING + (s + 1) * SLOT, &tmV, 0, row, bar_full + 8 * (s + 1));
                    meta[1 + u].x = cta; meta[1 + u].y = 0;
                    mbar_arrive(bar_ctrl + 8 * (1 + u));
                }
            } else {
                mbar_arrive(bar_full + 8);
            }
        }
        __syncthreads();
        const unsigned epoch = *s_epoch;
        const int par = epoch & 1;
        Ctr* ctr = g_ctr[par];
        int seq = (cta < NROLE) ? 6 : 2;
        int cur = (cta < NROLE) ? cta : -1;
        int pslot = 0;
        bool fresh = false;
        int nunit = 0;
        while (true) {
            const int s = seq % NSLOT;
            const uint32_t ph = ((seq / NSLOT) & 1) ^ 1;
            mbar_wait(bar_empty + 8 * s, ph);
            int unit = -1;
            while (true) {
                if (cur >= 0) {
                    unsigned old = 0;
                    if (lane == 0) old = atomicAdd(&ctr[cur].next, 1u);
                    old = __shfl_sync(0xffffffffu, old, 0) + 2u;
                    if (old < (unsigned)UNITS) { unit = (int)old; break; }
                    cur = -1;
                }
                float best = 0.f; int bestp = -1;
#pragma unroll
                for (int i = 0; i < 4; i++) {
                    const int p = ((lane + 32 * i) + cta * 37) & (NPAIR - 1);
                    uint4 v = ldg_relaxed4(reinterpret_cast<const unsigned*>(&ctr[p]));
                    const int rem = UNITS - 2 - (int)v.z;
                    if (rem > 0) {
                        float sc = (float)rem / (float)(v.x + 1u);
                        if (sc > best) { best = sc; bestp = p; }
                    }
                }
#pragma unroll
                for (int o = 16; o; o >>= 1) {
                    float ob = __shfl_xor_sync(0xffffffffu, best, o);
                    int op = __shfl_xor_sync(0xffffffffu, bestp, o);
                    int ol = lane ^ o;
                    if (ob > best || (ob == best && ol < lane)) { best = ob; bestp = op; }
                }
                bestp = __shfl_sync(0xffffffffu, bestp, 0);
                if (bestp < 0) break;
                cur = bestp; fresh = true;
            }
            const int us = (seq >> 1) % 3;
            if (unit < 0) {
                if (lane == 0) { meta[us].x = -1; mbar_arrive(bar_ctrl + 8 * us); }
                break;
            }
            if (lane == 0) {
                const int row = (cur * SK + unit * UKEYS) * 2;
                mbar_expect_tx(bar_full + 8 * s, SLOT);
                tma2d(sb + SM_RING + s * SLOT, &tmK, 0, row, bar_full + 8 * s);
                if (fresh) pslot = (int)atomicAdd(&ctr[cur].joined, 1u) + 1;
                meta[us].x = cur; meta[us].y = pslot;
                mbar_arrive(bar_ctrl + 8 * us);
                mbar_wait(bar_empty + 8 * (s + 1), ph);
                mbar_expect_tx(bar_full + 8 * (s + 1), SLOT);
                tma2d(sb + SM_RING + (s + 1) * SLOT, &tmV, 0, row, bar_full + 8 * (s + 1));
            }
            fresh = false;
            seq += 2;
            __syncwarp();
            if (cta == 0 && ++nunit == 8) {
                if (lane == 0) {
                    unsigned spins = 0;
                    while (ldg_relaxed1(&g_started[par]) < gridDim.x) { if (++spins > SPIN_LIMIT) TRAP_AT(__LINE__); }
                    g_started[par ^ 1] = 0;
                    g_epoch = epoch + 1;
                }
#pragma unroll
                for (int i = 0; i < 4; i++)
                    *reinterpret_cast<uint4*>(&g_ctr[par ^ 1][lane + 32 * i]) = make_uint4(0, 0, 0, 0);
            }
        }
        if (cta < NROLE && lane == 0) {
            const int hkv = cta >> 3, ns = cta & 7;
            const int gc = (36 * cta) & ~7;
            for (int i = 0; i < 6; i++) {
                const int sq = seq + i;
                const int s = sq % NSLOT;
                const uint32_t ph = ((sq / NSLOT) & 1) ^ 1;
                const uint32_t dst = sb + SM_RING + s * SLOT;
                const uint32_t fb = bar_full + 8 * s;
                mbar_wait(bar_empty + 8 * s, ph);
                if (i == 0) {
                    mbar_expect_tx(fb, 27648);
                    for (int r = 0; r < 3; r++) tma2d(dst + r * 9216, &tmO, 72 * ns, 256 * hkv + 64 * r, fb);
                } else if (i == 1) {
                    mbar_expect_tx(fb, 9216 + 15360);
                    tma2d(dst, &tmO, 72 * ns, 256 * hkv + 192, fb);
                    tma2d(dst + 9216, &tmG, gc, 0, fb);
                } else if (i == 2) {
                    mbar_expect_tx(fb, 30720);
                    tma2d(dst, &tmU, gc, 0, fb);
                    tma2d(dst + 15360, &tmG, gc, 192, fb);
                } else if (i == 3) {
                    mbar_expect_tx(fb, 30720);
                    tma2d(dst, &tmU, gc, 192, fb);
                    tma2d(dst + 15360, &tmG, gc, 384, fb);
                } else if (i == 4) {
                    mbar_expect_tx(fb, 15360 + 3 * 4608);
                    tma2d(dst, &tmU, gc, 384, fb);
                    for (int r = 0; r < 3; r++) tma2d(dst + 15360 + r * 5120, &tmD, 64 * r, 36 * cta, fb);
                } else {
                    mbar_expect_tx(fb, 6 * 4608);
                    for (int r = 0; r < 6; r++) tma2d(dst + r * 5120, &tmD, 64 * (3 + r), 36 * cta, fb);
                }
            }
        }
        return;
    }

    const int g = lane >> 2, t = lane & 3;
    if (tid == 0) {
        const unsigned e = ldg_relaxed1(&g_epoch);
        *s_epoch = e;
        atomicAdd(&g_started[e & 1], 1u);
    }
    const uint32_t bufA = sb + SM_BUFA;
    float* s_stat = reinterpret_cast<float*>(sp + SM_STAT);
    if (cta < 108) {
        const unsigned* cw = reinterpret_cast<const unsigned*>(prm.c) + warp * 288;
        unsigned cv[9];
#pragma unroll
        for (int i = 0; i < 9; i++) cv[i] = __ldg(cw + lane + 32 * i);
        if (cta < 36) {
            const unsigned* xw = reinterpret_cast<const unsigned*>(prm.x) + warp * 288;
            float xv[18];
#pragma unroll
            for (int i = 0; i < 9; i++) { unsigned w = __ldg(xw + lane + 32 * i); xv[2 * i] = bf_lo(w); xv[2 * i + 1] = bf_hi(w); }
            float mr, sr;
            ln_stats(xv, mr, sr);
            if (lane == 0) { s_stat[2 * warp] = mr; s_stat[2 * warp + 1] = sr; }
        }
#pragma unroll
        for (int i = 0; i < 9; i++) {
            float a = bf_lo(cv[i]), b = bf_hi(cv[i]);
            a = a / (1.0f + expf(-a));
            b = b / (1.0f + expf(-b));
            *reinterpret_cast<unsigned*>(sp + SM_BUFA + (warp * BUFA_PITCH + 2 * (lane + 32 * i)) * 2) = pack_bf2(a, b);
        }
    }
    __syncthreads();
    const unsigned epoch = *s_epoch;
    const int par = epoch & 1;
    const unsigned tag16 = epoch % 65535u + 1u;
    const unsigned tag2 = epoch % 3u + 1u;
    float4* s_red = reinterpret_cast<float4*>(sp + SM_RED);
    const uint32_t bA = bufA + (g * BUFA_PITCH + 2 * t) * 2;

    if (cta < 108) {
        mbar_wait(bar_full + 0, 0);
        const int tile = warp & 1, kq = warp >> 1;
        float acc[4] = {0.f, 0.f, 0.f, 0.f};
        const int kr = (lane & 7) + 8 * (lane >> 4);
        const uint32_t boxb = sb + ((lane >> 3) & 1) * 18432;
#pragma unroll
        for (int i = 0; i < 9; i++) {
            const int ks = kq * 9 + i;
            const int r = 16 * ks + kr;
            uint32_t a[4];
            ldsm4t(boxb + r * 32 + ((tile ^ ((r >> 2) & 1)) << 4), a);
            const uint32_t b0 = lds32(bA + ks * 32), b1 = lds32(bA + ks * 32 + 16);
            mma16816(acc, a, b0, b1);
        }
        s_red[warp * 32 + lane] = make_float4(acc[0], acc[1], acc[2], acc[3]);
        cons_sync();
        if (warp < 2) {
            float4 v = s_red[warp * 32 + lane];
#pragma unroll
            for (int k = 1; k < 4; k++) { float4 u = s_red[(warp + 2 * k) * 32 + lane]; v.x += u.x; v.y += u.y; v.z += u.z; v.w += u.w; }
            const int cl = 8 * warp + g;
            if (cta < 36) {
                const int col = 16 * cta + cl;
#pragma unroll
                for (int e = 0; e < 2; e++) {
                    const int b = 2 * t + e;
                    const float sa = bfr(e ? v.y : v.x), ca = bfr(e ? v.w : v.z);
                    const float xv = __bfloat162float(prm.x[b * DM + col]);
                    const float h = ln_mod(xv, s_stat[2 * b], s_stat[2 * b + 1], ca, sa);
                    stg_relaxed1(&g_h[b * DM + col], (bf_bits(h) << 16) | tag16);
                }
            } else {
                const int colA = 1152 + 32 * (cta - 36) + cl, colB = colA + 16;
                stg_relaxed1(&g_mod[(2 * t) * 3456 + colA], (bf_bits(v.x) << 16) | tag16);
                stg_relaxed1(&g_mod[(2 * t + 1) * 3456 + colA], (bf_bits(v.y) << 16) | tag16);
                stg_relaxed1(&g_mod[(2 * t) * 3456 + colB], (bf_bits(v.z) << 16) | tag16);
                stg_relaxed1(&g_mod[(2 * t + 1) * 3456 + colB], (bf_bits(v.w) << 16) | tag16);
            }
        }
    }
    if (cta < NROLE) {
        uint2 hv[9];
        poll_row16<9>(g_h + warp * DM, lane, tag16, hv);
        cons_sync();
#pragma unroll
        for (int i = 0; i < 9; i++)
            *reinterpret_cast<unsigned*>(sp + SM_BUFA + (warp * BUFA_PITCH + 2 * (lane + 32 * i)) * 2) = pack_hi(hv[i].x, hv[i].y);
        cons_sync();
        mbar_wait(bar_full + 8, 0);
        const int tile = warp & 1, kq = warp >> 1;
        float acc[4] = {0.f, 0.f, 0.f, 0.f};
        const int kr = (lane & 7) + 8 * (lane >> 4);
        const int ch = 2 * tile + ((lane >> 3) & 1);
#pragma unroll
        for (int i = 0; i < 9; i++) {
            const int ks = kq * 9 + i;
            const int r = 16 * ks + kr;
            uint32_t a[4];
            ldsm4t(sb + 36864 + r * 64 + ((ch ^ ((r >> 1) & 3)) << 4), a);
            const uint32_t b0 = lds32(bA + ks * 32), b1 = lds32(bA + ks * 32 + 16);
            mma16816(acc, a, b0, b1);
        }
        s_red[warp * 32 + lane] = make_float4(acc[0], acc[1], acc[2], acc[3]);
        cons_sync();
        if (warp < 2) {
            float4 v = s_red[warp * 32 + lane];
#pragma unroll
            for (int k = 1; k < 4; k++) { float4 u = s_red[(warp + 2 * k) * 32 + lane]; v.x += u.x; v.y += u.y; v.z += u.z; v.w += u.w; }
            const int col = 32 * cta + 16 * warp + g;
            stg_relaxed1(&g_q[(2 * t) * 4096 + col], (bf_bits(v.x) << 16) | tag16);
            stg_relaxed1(&g_q[(2 * t + 1) * 4096 + col], (bf_bits(v.y) << 16) | tag16);
            stg_relaxed1(&g_q[(2 * t) * 4096 + col + 8], (bf_bits(v.z) << 16) | tag16);
            stg_relaxed1(&g_q[(2 * t + 1) * 4096 + col + 8], (bf_bits(v.w) << 16) | tag16);
        }
    }
    __syncwarp();
    if (lane == 0) { mbar_arrive(bar_empty + 0); mbar_arrive(bar_empty + 8); }

    int seq = 2;
    {
        uint32_t kpre[2], vpre[2];
        {
            const int key = (lane & 7) + 8 * ((lane >> 3) & 1), cs = lane >> 4;
#pragma unroll
            for (int h = 0; h < 2; h++) {
                const int r = 2 * (16 * warp + key) + h;
                kpre[h] = r * 128 + ((cs ^ (r & 7)) << 4);
            }
            const int kr = (lane & 7), hi = lane >> 4, cv = (lane >> 3) & 1;
            const int vkey = (kr >> 1) + 8 * (kr & 1) + 4 * hi;
#pragma unroll
            for (int h = 0; h < 2; h++) {
                const int r = 2 * (16 * warp + vkey) + h;
                vpre[h] = r * 128 + ((cv ^ (r & 7)) << 4);
            }
        }
        uint32_t qf[8][2];
        float o[8][4];
        float m = -INFINITY, l = 0.f;
        int cur = -1, pslot = 0, cnt = 0;
        float* scr_o = reinterpret_cast<float*>(sp + SM_SCR);
        float* scr_ml = reinterpret_cast<float*>(sp + SM_ML);
        while (true) {
            const int us = (seq >> 1) % 3;
            const uint32_t cph = (((seq >> 1) - 1) / 3) & 1;
            mbar_wait(bar_ctrl + 8 * us, cph);
            const int np = meta[us].x, nslot = meta[us].y;
            if (np != cur) {
                if (cur >= 0) {
#pragma unroll
                    for (int of = 4; of <= 16; of <<= 1) l += __shfl_xor_sync(0xffffffffu, l, of);
                    if (t == 0) {
#pragma unroll
                        for (int mt = 0; mt < 8; mt++) {
                            scr_o[(warp * 2 + 0) * 128 + 16 * mt + g] = o[mt][0];
                            scr_o[(warp * 2 + 1) * 128 + 16 * mt + g] = o[mt][1];
                            scr_o[(warp * 2 + 0) * 128 + 16 * mt + g + 8] = o[mt][2];
                            scr_o[(warp * 2 + 1) * 128 + 16 * mt + g + 8] = o[mt][3];
                        }
                    }
                    if (lane < 2) { scr_ml[(warp * 2 + lane) * 2] = m; scr_ml[(warp * 2 + lane) * 2 + 1] = l; }
                    cons_sync();
                    {
                        const int h = tid >> 7, d = tid & 127;
                        float M = -INFINITY;
#pragma unroll
                        for (int w = 0; w < 8; w++) M = fmaxf(M, scr_ml[(w * 2 + h) * 2]);
                        float O = 0.f, L = 0.f;
#pragma unroll
                        for (int w = 0; w < 8; w++) {
                            const float f = ex2((scr_ml[(w * 2 + h) * 2] - M) * LOG2E);
                            O += f * scr_o[(w * 2 + h) * 128 + d];
                            L += f * scr_ml[(w * 2 + h) * 2 + 1];
                        }
                        float* rec = g_part + ((size_t)cur * MAXS + pslot) * PSTRIDE;
                        rec[tid] = O;
                        if (d == 0) { rec[256 + 2 * h] = M; rec[257 + 2 * h] = L; }
                    }
                    cons_sync();
                    if (tid == 0) {
                        __threadfence();
                        atomicAdd(&g_ctr[par][cur].done, (unsigned)cnt);
                    }
                }
                if (np < 0) break;
                cur = np; pslot = nslot; cnt = 0;
                m = -INFINITY; l = 0.f;
#pragma unroll
                for (int mt = 0; mt < 8; mt++) { o[mt][0] = o[mt][1] = o[mt][2] = o[mt][3] = 0.f; }
                const unsigned* qb = g_q + (cur >> 4) * 4096 + (cur & 15) * 256 + (g & 1) * 128 + 2 * t;
                unsigned spins = 0;
                while (true) {
                    bool ok = true;
#pragma unroll
                    for (int ks = 0; ks < 8; ks++) {
                        uint2 a = ldg_relaxed2(qb + 16 * ks), b = ldg_relaxed2(qb + 16 * ks + 8);
                        ok = ok && ((a.x & 0xffffu) == tag16) && ((a.y & 0xffffu) == tag16) &&
                             ((b.x & 0xffffu) == tag16) && ((b.y & 0xffffu) == tag16);
                        qf[ks][0] = pack_hi(a.x, a.y);
                        qf[ks][1] = pack_hi(b.x, b.y);
                    }
                    if (__all_sync(0xffffffffu, ok)) break;
                    if (++spins > SPIN_LIMIT) TRAP_AT(__LINE__);
                    __nanosleep(100);
                }
            }
            const int sK = seq % NSLOT;
            const uint32_t ph = (seq / NSLOT) & 1;
            const uint32_t kb = sb + SM_RING + sK * SLOT, vb = kb + SLOT;
            mbar_wait(bar_full + 8 * sK, ph);
            float c0[4] = {0.f, 0.f, 0.f, 0.f}, c1[4] = {0.f, 0.f, 0.f, 0.f};
#pragma unroll
            for (int ks = 0; ks < 8; ks += 2) {
                uint32_t a[4], b[4];
                ldsm4(kb + (kpre[ks >> 2] ^ ((ks & 3) << 5)), a);
                ldsm4(kb + (kpre[(ks + 1) >> 2] ^ (((ks + 1) & 3) << 5)), b);
                mma16816(c0, a, qf[ks][0], qf[ks][1]);
                mma16816(c1, b, qf[ks + 1][0], qf[ks + 1][1]);
            }
            __syncwarp();
            if (lane == 0) mbar_arrive(bar_empty + 8 * sK);
            float s0 = (t & 1) ? (c0[1] + c1[1]) : (c0[0] + c1[0]);
            float s1 = (t & 1) ? (c0[3] + c1[3]) : (c0[2] + c1[2]);
            s0 = bfr(bfr(s0) * QSCALE);
            s1 = bfr(bfr(s1) * QSCALE);
            float bm = fmaxf(s0, s1);
            if (__any_sync(0xffffffffu, bm > m)) {
#pragma unroll
                for (int of = 4; of <= 16; of <<= 1) bm = fmaxf(bm, __shfl_xor_sync(0xffffffffu, bm, of));
                const float mn = fmaxf(m, bm);
                const float al = ex2((m - mn) * LOG2E);
                m = mn; l *= al;
                const float alo = __shfl_xor_sync(0xffffffffu, al, 1);
                const float a0 = (t & 1) ? alo : al, a1 = (t & 1) ? al : alo;
#pragma unroll
                for (int mt = 0; mt < 8; mt++) { o[mt][0] *= a0; o[mt][1] *= a1; o[mt][2] *= a0; o[mt][3] *= a1; }
            }
            const float p0 = ex2((s0 - m) * LOG2E), p1 = ex2((s1 - m) * LOG2E);
            l += p0 + p1;
            const unsigned pk = pack_bf2(p0, p1);
            const unsigned pb0 = __shfl_sync(0xffffffffu, pk, 4 * t + (g & 1));
            const unsigned pb1 = __shfl_sync(0xffffffffu, pk, 4 * (t + 4) + (g & 1));
            mbar_wait(bar_full + 8 * (sK + 1), ph);
#pragma unroll
            for (int mt = 0; mt < 8; mt++) {
                uint32_t a[4];
                ldsm4t(vb + (vpre[mt >> 2] ^ ((mt & 3) << 5)), a);
                mma16816(o[mt], a, pb0, pb1);
            }
            __syncwarp();
            if (lane == 0) mbar_arrive(bar_empty + 8 * (sK + 1));
            cnt++;
            seq += 2;
        }
    }
    if (cta >= NROLE) return;

    const int hkv = cta >> 3, ns = cta & 7;
    {
        const int p = warp * HKV + hkv;
        unsigned nj;
        {
            unsigned spins = 0;
            while (true) {
                uint2 v = ldg_relaxed2(reinterpret_cast<const unsigned*>(&g_ctr[par][p]));
                if (v.y == (unsigned)UNITS) { nj = v.x + 1; break; }
                if (++spins > SPIN_LIMIT) TRAP_AT(__LINE__);
                __nanosleep(32);
            }
            __threadfence();
        }
        const int h = lane >> 4;
        const float* rec = g_part + (size_t)p * MAXS * PSTRIDE;
        float M = -INFINITY, L = 0.f;
        float O[8];
#pragma unroll
        for (int i = 0; i < 8; i++) O[i] = 0.f;
        for (unsigned s = 0; s < nj; s++) {
            const float* r = rec + (size_t)s * PSTRIDE;
            const float4 a = __ldcg(reinterpret_cast<const float4*>(r + lane * 8));
            const float4 b = __ldcg(reinterpret_cast<const float4*>(r + lane * 8 + 4));
            const float2 ml = __ldcg(reinterpret_cast<const float2*>(r + 256 + 2 * h));
            const float Mn = fmaxf(M, ml.x);
            const float fo = ex2((M - Mn) * LOG2E), fn = ex2((ml.x - Mn) * LOG2E);
            M = Mn;
            L = L * fo + ml.y * fn;
            O[0] = O[0] * fo + a.x * fn; O[1] = O[1] * fo + a.y * fn; O[2] = O[2] * fo + a.z * fn; O[3] = O[3] * fo + a.w * fn;
            O[4] = O[4] * fo + b.x * fn; O[5] = O[5] * fo + b.y * fn; O[6] = O[6] * fo + b.z * fn; O[7] = O[7] * fo + b.w * fn;
        }
        uint4 w;
        w.x = pack_bf2(O[0] / L, O[1] / L); w.y = pack_bf2(O[2] / L, O[3] / L);
        w.z = pack_bf2(O[4] / L, O[5] / L); w.w = pack_bf2(O[6] / L, O[7] / L);
        *reinterpret_cast<uint4*>(sp + SM_SCR + (warp * BUFO_PITCH + lane * 8) * 2) = w;
    }
    cons_sync();
    if (warp < 5) {
        const int s0 = seq % NSLOT, s1 = (seq + 1) % NSLOT;
        mbar_wait(bar_full + 8 * s0, (seq / NSLOT) & 1);
        mbar_wait(bar_full + 8 * s1, ((seq + 1) / NSLOT) & 1);
        const uint32_t w0 = sb + SM_RING + s0 * SLOT, w1 = sb + SM_RING + s1 * SLOT;
        const uint32_t bO = sb + SM_SCR + (g * BUFO_PITCH + 2 * t) * 2;
        const int kr = (lane & 7) + 8 * (lane >> 4);
        int cb = 16 * warp + 8 * ((lane >> 3) & 1);
        if (cb > 64) cb = 64;
        float acc[2][4] = {{0.f, 0.f, 0.f, 0.f}, {0.f, 0.f, 0.f, 0.f}};
#pragma unroll
        for (int ks = 0; ks < 16; ks++) {
            const int r = 16 * ks + kr;
            const uint32_t addr = (ks < 12 ? w0 + r * 144 : w1 + (r - 192) * 144) + cb * 2;
            uint32_t a[4];
            ldsm4t(addr, a);
            mma16816(acc[ks & 1], a, lds32(bO + ks * 32), lds32(bO + ks * 32 + 16));
        }
        unsigned* dst = g_wop + (size_t)hkv * (DM * NB) + (72 * ns + 16 * warp + g) * 8 + 2 * t;
        stg_relaxed2(dst, (__float_as_uint(acc[0][0] + acc[1][0]) & ~3u) | tag2, (__float_as_uint(acc[0][1] + acc[1][1]) & ~3u) | tag2);
        if (warp < 4)
            stg_relaxed2(dst + 64, (__float_as_uint(acc[0][2] + acc[1][2]) & ~3u) | tag2, (__float_as_uint(acc[0][3] + acc[1][3]) & ~3u) | tag2);
    }
    if (warp < 5) {
        const int src = lane & 15, ch = 2 * warp + (lane >> 4);
        if (warp < 4 || lane < 16) {
            const unsigned amask = warp < 4 ? 0xffffffffu : 0x0000ffffu;
            const int v0 = ns * 576 + 36 * hkv + 4 * ch;
            const int vi = v0 + (src & 3);
            const int col = vi >> 3, b = vi & 7;
            float xv = 0.f; unsigned gaw = 0;
            if (src < 4) {
                xv = __bfloat162float(prm.x[b * DM + col]);
                unsigned spins = 0;
                while (((gaw = ldg_relaxed1(&g_mod[b * 3456 + 2 * DM + col])) & 0xffffu) != tag16) { if (++spins > SPIN_LIMIT) TRAP_AT(__LINE__); }
            }
            const unsigned* ptr = g_wop + (size_t)src * (DM * NB) + v0;
            uint4 v;
            unsigned spins = 0;
            while (true) {
                v = ldg_relaxed4(ptr);
                if ((v.x & 3u) == tag2 && (v.y & 3u) == tag2 && (v.z & 3u) == tag2 && (v.w & 3u) == tag2) break;
                if (++spins > SPIN_LIMIT) TRAP_AT(__LINE__);
            }
            float f0 = __uint_as_float(v.x & ~3u), f1 = __uint_as_float(v.y & ~3u), f2 = __uint_as_float(v.z & ~3u), f3 = __uint_as_float(v.w & ~3u);
#pragma unroll
            for (int of = 1; of <= 8; of <<= 1) {
                f0 += __shfl_xor_sync(amask, f0, of); f1 += __shfl_xor_sync(amask, f1, of);
                f2 += __shfl_xor_sync(amask, f2, of); f3 += __shfl_xor_sync(amask, f3, of);
            }
            if (src < 4) {
                const float a = bfr(src == 0 ? f0 : src == 1 ? f1 : src == 2 ? f2 : f3);
                const float x2 = xv + bfr(bf_hi(gaw) * a);
                stg_relaxed1(&g_x2[b * DM + col], (bf_bits(x2) << 16) | tag16);
            }
        }
    }
    {
        uint2 cbv[9], sbv[9], xv2[9];
        poll_row16<9>(g_mod + warp * 3456 + 4 * DM, lane, tag16, cbv);
        poll_row16<9>(g_mod + warp * 3456 + 3 * DM, lane, tag16, sbv);
        poll_row16<9>(g_x2 + warp * DM, lane, tag16, xv2);
        float xf[18];
#pragma unroll
        for (int i = 0; i < 9; i++) { xf[2 * i] = bf_hi(xv2[i].x); xf[2 * i + 1] = bf_hi(xv2[i].y); }
        float mr, sr;
        ln_stats(xf, mr, sr);
#pragma unroll
        for (int i = 0; i < 9; i++) {
            const float h0 = ln_mod(xf[2 * i], mr, sr, bf_hi(cbv[i].x), bf_hi(sbv[i].x));
            const float h1 = ln_mod(xf[2 * i + 1], mr, sr, bf_hi(cbv[i].y), bf_hi(sbv[i].y));
            *reinterpret_cast<unsigned*>(sp + SM_BUFA + (warp * BUFA_PITCH + 2 * (lane + 32 * i)) * 2) = pack_bf2(h0, h1);
        }
        if (tid < 48) *reinterpret_cast<unsigned*>(sp + SM_ACT + ((tid / 6) * ACT_PITCH + 36 + 2 * (tid % 6)) * 2) = 0;
    }
    cons_sync();
    if (warp < 5) {
        uint32_t sl[4];
#pragma unroll
        for (int i = 0; i < 4; i++) {
            const int sq = seq + 1 + i;
            mbar_wait(bar_full + 8 * (sq % NSLOT), (sq / NSLOT) & 1);
            sl[i] = sb + SM_RING + (sq % NSLOT) * SLOT;
        }
        const bool isup = (lane >> 3) & 1;
        const int kr = (lane & 7) + 8 * (lane >> 4);
        uint32_t base[3];
        base[0] = isup ? sl[1] : sl[0] + 9216;
        base[1] = isup ? sl[2] : sl[1] + 15360;
        base[2] = isup ? sl[3] : sl[2] + 15360;
        float acc[4][4];
#pragma unroll
        for (int i = 0; i < 4; i++) acc[i][0] = acc[i][1] = acc[i][2] = acc[i][3] = 0.f;
#pragma unroll
        for (int ks = 0; ks < 36; ks++) {
            const int r = (16 * ks) % 192 + kr;
            uint32_t a[4];
            ldsm4t(base[ks / 12] + r * 80 + warp * 16, a);
            mma16816(acc[ks & 3], a, lds32(bA + ks * 32), lds32(bA + ks * 32 + 16));
        }
        const int cl = 8 * warp + g - 4 * (cta & 1);
#pragma unroll
        for (int e = 0; e < 2; e++) {
            const float gt = bfr(acc[0][e] + acc[1][e] + acc[2][e] + acc[3][e]);
            const float up = bfr(acc[0][2 + e] + acc[1][2 + e] + acc[2][2 + e] + acc[3][2 + e]);
            const float inner = 0.7978845608028654f * (gt + 0.044715f * gt * gt * gt);
            const float ge = bfr(0.5f * gt * (1.0f + tanhf(inner)));
            if (cl >= 0 && cl < 36)
                *reinterpret_cast<__nv_bfloat16*>(sp + SM_ACT + ((2 * t + e) * ACT_PITCH + cl) * 2) = __float2bfloat16_rn(ge * up);
        }
    }
    cons_sync();
    {
        const int s4 = (seq + 4) % NSLOT, s5 = (seq + 5) % NSLOT;
        mbar_wait(bar_full + 8 * s4, ((seq + 4) / NSLOT) & 1);
        mbar_wait(bar_full + 8 * s5, ((seq + 5) / NSLOT) & 1);
        const uint32_t d4 = sb + SM_RING + s4 * SLOT + 15360, d5 = sb + SM_RING + s5 * SLOT;
        const uint32_t bAct = sb + SM_ACT + (g * ACT_PITCH + 2 * t) * 2;
        uint32_t bf[3][2];
#pragma unroll
        for (int ks = 0; ks < 3; ks++) { bf[ks][0] = lds32(bAct + ks * 32); bf[ks][1] = lds32(bAct + ks * 32 + 16); }
        const int kr = (lane & 7) + 8 * (lane >> 4), cs = (lane >> 3) & 1;
        for (int tile = warp; tile < 36; tile += 8) {
            const int cbk = tile >> 2;
            const uint32_t box = cbk < 3 ? d4 + cbk * 5120 : d5 + (cbk - 3) * 5120;
            const int ch = (tile & 3) * 2 + cs;
            float acc[4] = {0.f, 0.f, 0.f, 0.f};
#pragma unroll
            for (int ks = 0; ks < 3; ks++) {
                int r = 16 * ks + kr;
                if (r > 35) r = 35;
                uint32_t a[4];
                ldsm4t(box + r * 128 + ((ch ^ (r & 7)) << 4), a);
                mma16816(acc, a, bf[ks][0], bf[ks][1]);
            }
            unsigned* dst = g_dnp + (size_t)cta * (DM * NB) + (16 * tile + g) * 8 + 2 * t;
            stg_relaxed2(dst, (__float_as_uint(acc[0]) & ~3u) | tag2, (__float_as_uint(acc[1]) & ~3u) | tag2);
            stg_relaxed2(dst + 64, (__float_as_uint(acc[2]) & ~3u) | tag2, (__float_as_uint(acc[3]) & ~3u) | tag2);
        }
    }
    if (cta < 72) {
        unsigned x2w = 0, gbw = 0;
        if (tid < 64) {
            const int col = 8 * cta + (tid >> 3), b = tid & 7;
            x2w = ldg_relaxed1(&g_x2[b * DM + col]);
            unsigned spins = 0;
            while (((gbw = ldg_relaxed1(&g_mod[b * 3456 + 5 * DM + col])) & 0xffffu) != tag16) { if (++spins > SPIN_LIMIT) TRAP_AT(__LINE__); }
        }
        const int ch = lane & 15, sl = lane >> 4;
        const unsigned* ptr = g_dnp + (size_t)(16 * warp + sl) * (DM * NB) + 64 * cta + 4 * ch;
        uint4 v[8];
#pragma unroll
        for (int i = 0; i < 8; i++) v[i] = ldg_relaxed4(ptr + (size_t)(2 * i) * (DM * NB));
        unsigned spins = 0;
        while (true) {
            bool ok = true;
#pragma unroll
            for (int i = 0; i < 8; i++) {
                if ((v[i].x & 3u) != tag2 || (v[i].y & 3u) != tag2 || (v[i].z & 3u) != tag2 || (v[i].w & 3u) != tag2) {
                    v[i] = ldg_relaxed4(ptr + (size_t)(2 * i) * (DM * NB));
                    ok = false;
                }
            }
            if (ok) break;
            if (++spins > SPIN_LIMIT) TRAP_AT(__LINE__);
        }
        float f[4] = {0.f, 0.f, 0.f, 0.f};
#pragma unroll
        for (int i = 0; i < 8; i++) {
            f[0] += __uint_as_float(v[i].x & ~3u); f[1] += __uint_as_float(v[i].y & ~3u);
            f[2] += __uint_as_float(v[i].z & ~3u); f[3] += __uint_as_float(v[i].w & ~3u);
        }
#pragma unroll
        for (int e = 0; e < 4; e++) f[e] += __shfl_xor_sync(0xffffffffu, f[e], 16);
        if (lane < 16) s_red[warp * 16 + ch] = make_float4(f[0], f[1], f[2], f[3]);
        cons_sync();
        if (tid < 64) {
            const float* r = reinterpret_cast<const float*>(s_red);
            float s = 0.f;
#pragma unroll
            for (int w = 0; w < 8; w++) s += r[w * 64 + tid];
            const float o = bf_hi(x2w) + bfr(bf_hi(gbw) * bfr(s));
            prm.out[(tid & 7) * DM + 8 * cta + (tid >> 3)] = __float2bfloat16_rn(o);
        }
    }
}

typedef CUresult (*EncodeFn)(CUtensorMap*, CUtensorMapDataType, cuuint32_t, void*, const cuuint64_t*, const cuuint64_t*,
                             const cuuint32_t*, const cuuint32_t*, CUtensorMapInterleave, CUtensorMapSwizzle,
                             CUtensorMapL2promotion, CUtensorMapFloatOOBfill);

bool make_map(EncodeFn fn, CUtensorMap* m, const void* ptr, uint64_t inner, uint64_t outer, uint64_t stride_bytes,
              uint32_t box_inner, uint32_t box_outer, CUtensorMapSwizzle sw, CUtensorMapL2promotion promo) {
    cuuint64_t dims[2] = {inner, outer};
    cuuint64_t strides[1] = {stride_bytes};
    cuuint32_t box[2] = {box_inner, box_outer};
    cuuint32_t es[2] = {1, 1};
    return fn(m, CU_TENSOR_MAP_DATA_TYPE_BFLOAT16, 2, const_cast<void*>(ptr), dims, strides, box, es,
              CU_TENSOR_MAP_INTERLEAVE_NONE, sw, promo, CU_TENSOR_MAP_FLOAT_OOB_FILL_NONE) == CUDA_SUCCESS;
}

}

extern "C" void kernel_launch(void* const* d_in, const int* in_sizes, int n_in, void* d_out, int out_size) {
    (void)in_sizes; (void)n_in; (void)out_size;
    static EncodeFn encode = nullptr;
    static int num_sms = 0;
    if (!encode) {
        void* fn = nullptr;
        cudaDriverEntryPointQueryResult qres;
        cudaGetDriverEntryPoint("cuTensorMapEncodeTiled", &fn, cudaEnableDefault, &qres);
        encode = (EncodeFn)fn;
        int dev = 0;
        cudaGetDevice(&dev);
        cudaDeviceGetAttribute(&num_sms, cudaDevAttrMultiProcessorCount, dev);
        cudaFuncSetAttribute(fused_kernel, cudaFuncAttributeMaxDynamicSharedMemorySize, SMEM_BYTES);
    }
    CUtensorMap tmK, tmV, tmMod, tmQ, tmO, tmG, tmU, tmD;
    const uint64_t kvrows = (uint64_t)NB * HKV * SK * 2;
    make_map(encode, &tmK, d_in[1], 64, kvrows, 128, 64, 256, CU_TENSOR_MAP_SWIZZLE_128B, CU_TENSOR_MAP_L2_PROMOTION_L2_256B);
    make_map(encode, &tmV, d_in[2], 64, kvrows, 128, 64, 256, CU_TENSOR_MAP_SWIZZLE_128B, CU_TENSOR_MAP_L2_PROMOTION_L2_256B);
    make_map(encode, &tmQ, d_in[3], 4096, DM, 8192, 32, 192, CU_TENSOR_MAP_SWIZZLE_64B, CU_TENSOR_MAP_L2_PROMOTION_L2_128B);
    make_map(encode, &tmO, d_in[4], DM, 4096, DM * 2, 72, 64, CU_TENSOR_MAP_SWIZZLE_NONE, CU_TENSOR_MAP_L2_PROMOTION_L2_128B);
    make_map(encode, &tmG, d_in[6], FF, DM, FF * 2, 40, 192, CU_TENSOR_MAP_SWIZZLE_NONE, CU_TENSOR_MAP_L2_PROMOTION_L2_128B);
    make_map(encode, &tmU, d_in[7], FF, DM, FF * 2, 40, 192, CU_TENSOR_MAP_SWIZZLE_NONE, CU_TENSOR_MAP_L2_PROMOTION_L2_128B);
    make_map(encode, &tmD, d_in[8], DM, FF, DM * 2, 64, 36, CU_TENSOR_MAP_SWIZZLE_128B, CU_TENSOR_MAP_L2_PROMOTION_L2_128B);
    make_map(encode, &tmMod, d_in[10], 6 * DM, DM, 6 * DM * 2, 16, 192, CU_TENSOR_MAP_SWIZZLE_32B, CU_TENSOR_MAP_L2_PROMOTION_L2_128B);
    Params prm;
    prm.x = (const __nv_bfloat16*)d_in[0];
    prm.c = (const __nv_bfloat16*)d_in[9];
    prm.out = (__nv_bfloat16*)d_out;
    int grid = num_sms < MAXCTA ? num_sms : MAXCTA;
    fused_kernel<<<grid, NTHREADS, SMEM_BYTES>>>(tmK, tmV, tmMod, tmQ, tmO, tmG, tmU, tmD, prm);
}
```

```cpp
#include <cuda_runtime.h>
#include <cuda_bf16.h>
#include <cuda.h>
#include <stdint.h>

namespace {

constexpr int NB = 8;
constexpr int DM = 576;
constexpr int HKV = 16;
constexpr int SK = 8192;
constexpr int DH = 128;
constexpr int FF = 4608;
constexpr int NPAIR = NB * HKV;
constexpr int UKEYS = 128;
constexpr int UNITS = SK / UKEYS;
constexpr int SLOT = 32768;
constexpr int NSLOT = 6;
constexpr int NROLE = 128;
constexpr int MAXCTA = 132;
constexpr int MAXS = MAXCTA + 1;
constexpr int PSTRIDE = 264;
constexpr int NCONS = 256;
constexpr int NTHREADS = 288;

constexpr int SM_SCR = 0;
constexpr int SM_RING = 8192;
constexpr int SM_BUFA = SM_RING + NSLOT * SLOT;
constexpr int BUFA_PITCH = 584;
constexpr int SM_RED = SM_BUFA + 8 * BUFA_PITCH * 2;
constexpr int SM_ACT = SM_RED + 4096;
constexpr int ACT_PITCH = 56;
constexpr int SM_ML = SM_ACT + 8 * ACT_PITCH * 2;
constexpr int SM_STAT = SM_ML + 128;
constexpr int SM_META = SM_STAT + 64;
constexpr int SM_BAR = SM_META + 32;
constexpr int SM_EPOCH = SM_BAR + 16 * 8;
constexpr int SM_TOTAL = SM_EPOCH + 16;
constexpr int SMEM_BYTES = SM_TOTAL + 1024;
constexpr int BUFO_PITCH = 264;

struct __align__(16) Ctr { unsigned joined, done, next, pad; };

__device__ Ctr g_ctr[2][NPAIR];
__device__ unsigned g_epoch;
__device__ unsigned g_started[2];
__device__ __align__(16) unsigned g_h[NB * DM];
__device__ __align__(16) unsigned g_mod[NB * 6 * DM];
__device__ __align__(16) unsigned g_q[NB * 4096];
__device__ __align__(16) float g_part[(size_t)NPAIR * MAXS * PSTRIDE];
__device__ __align__(16) unsigned g_wop[HKV * DM * NB];
__device__ __align__(16) unsigned g_x2[NB * DM];
__device__ __align__(16) unsigned g_dnp[(size_t)NROLE * DM * NB];

struct Params {
    const __nv_bfloat16* x;
    const __nv_bfloat16* c;
    __nv_bfloat16* out;
};

#define TRAP_AT(line) __trap()
#define TS(i)
#define TSV(i, v)

__device__ __forceinline__ uint32_t smem_u32(const void* p) { return (uint32_t)__cvta_generic_to_shared(p); }
__device__ __forceinline__ void mbar_init(uint32_t bar, uint32_t cnt) {
    asm volatile("mbarrier.init.shared::cta.b64 [%0], %1;" ::"r"(bar), "r"(cnt) : "memory");
}
__device__ __forceinline__ void mbar_expect_tx(uint32_t bar, uint32_t bytes) {
    asm volatile("mbarrier.arrive.expect_tx.shared::cta.b64 _, [%0], %1;" ::"r"(bar), "r"(bytes) : "memory");
}
__device__ __forceinline__ void mbar_arrive(uint32_t bar) {
    asm volatile("mbarrier.arrive.shared::cta.b64 _, [%0];" ::"r"(bar) : "memory");
}
__device__ __forceinline__ bool mbar_try(uint32_t bar, uint32_t parity) {
    uint32_t ok;
    asm volatile(
        "{\n.reg .pred p;\n"
        "mbarrier.try_wait.parity.shared::cta.b64 p, [%1], %2;\n"
        "selp.u32 %0, 1, 0, p;\n}\n"
        : "=r"(ok) : "r"(bar), "r"(parity) : "memory");
    return ok != 0;
}
__device__ __forceinline__ void mbar_wait(uint32_t bar, uint32_t parity) {
    unsigned spins = 0;
    while (!mbar_try(bar, parity)) {
        if (++spins > (1u << 26)) TRAP_AT(__LINE__);
    }
}
__device__ __forceinline__ void tma2d(uint32_t dst, const CUtensorMap* map, int c0, int c1, uint32_t bar) {
    asm volatile(
        "cp.async.bulk.tensor.2d.shared::cluster.global.mbarrier::complete_tx::bytes [%0], [%1, {%3, %4}], [%2];"
        ::"r"(dst), "l"((uint64_t)map), "r"(bar), "r"(c0), "r"(c1) : "memory");
}
__device__ __forceinline__ void ldsm4(uint32_t addr, uint32_t (&r)[4]) {
    asm volatile("ldmatrix.sync.aligned.m8n8.x4.shared.b16 {%0,%1,%2,%3}, [%4];"
                 : "=r"(r[0]), "=r"(r[1]), "=r"(r[2]), "=r"(r[3]) : "r"(addr) : "memory");
}
__device__ __forceinline__ void ldsm4t(uint32_t addr, uint32_t (&r)[4]) {
    asm volatile("ldmatrix.sync.aligned.m8n8.x4.trans.shared.b16 {%0,%1,%2,%3}, [%4];"
                 : "=r"(r[0]), "=r"(r[1]), "=r"(r[2]), "=r"(r[3]) : "r"(addr) : "memory");
}
__device__ __forceinline__ void mma16816(float (&c)[4], const uint32_t (&a)[4], uint32_t b0, uint32_t b1) {
    asm volatile(
        "mma.sync.aligned.m16n8k16.row.col.f32.bf16.bf16.f32 {%0,%1,%2,%3}, {%4,%5,%6,%7}, {%8,%9}, {%0,%1,%2,%3};"
        : "+f"(c[0]), "+f"(c[1]), "+f"(c[2]), "+f"(c[3])
        : "r"(a[0]), "r"(a[1]), "r"(a[2]), "r"(a[3]), "r"(b0), "r"(b1));
}
__device__ __forceinline__ void cons_sync() { asm volatile("bar.sync 1, 256;" ::: "memory"); }
__device__ __forceinline__ uint32_t lds32(uint32_t addr) {
    uint32_t v; asm volatile("ld.shared.u32 %0, [%1];" : "=r"(v) : "r"(addr) : "memory"); return v;
}
__device__ __forceinline__ uint2 ldg_relaxed2(const unsigned* p) {
    uint2 v; asm volatile("ld.relaxed.gpu.global.v2.u32 {%0,%1}, [%2];" : "=r"(v.x), "=r"(v.y) : "l"(p) : "memory"); return v;
}
__device__ __forceinline__ uint4 ldg_relaxed4(const unsigned* p) {
    uint4 v; asm volatile("ld.relaxed.gpu.global.v4.u32 {%0,%1,%2,%3}, [%4];"
                          : "=r"(v.x), "=r"(v.y), "=r"(v.z), "=r"(v.w) : "l"(p) : "memory"); return v;
}
__device__ __forceinline__ unsigned ldg_relaxed1(const unsigned* p) {
    unsigned v; asm volatile("ld.relaxed.gpu.global.u32 %0, [%1];" : "=r"(v) : "l"(p) : "memory"); return v;
}
__device__ __forceinline__ void stg_relaxed1(unsigned* p, unsigned v) {
    asm volatile("st.relaxed.gpu.global.u32 [%0], %1;" ::"l"(p), "r"(v) : "memory");
}
__device__ __forceinline__ void stg_relaxed2(unsigned* p, unsigned a, unsigned b) {
    asm volatile("st.relaxed.gpu.global.v2.u32 [%0], {%1,%2};" ::"l"(p), "r"(a), "r"(b) : "memory");
}
__device__ __forceinline__ float ex2(float x) { float y; asm("ex2.approx.ftz.f32 %0, %1;" : "=f"(y) : "f"(x)); return y; }

__device__ __forceinline__ float bfr(float x) { return __bfloat162float(__float2bfloat16_rn(x)); }
__device__ __forceinline__ unsigned bf_bits(float x) { return (unsigned)__bfloat16_as_ushort(__float2bfloat16_rn(x)); }
__device__ __forceinline__ float bf_hi(unsigned w) { return __uint_as_float(w & 0xffff0000u); }
__device__ __forceinline__ float bf_lo(unsigned w) { return __uint_as_float(w << 16); }
__device__ __forceinline__ unsigned pack_hi(unsigned lo_word, unsigned hi_word) {
    return __byte_perm(lo_word, hi_word, 0x7632);
}
__device__ __forceinline__ unsigned pack_bf2(float lo, float hi) {
    unsigned r; asm("cvt.rn.bf16x2.f32 %0, %1, %2;" : "=r"(r) : "f"(hi), "f"(lo)); return r;
}
constexpr float LOG2E = 1.4426950408889634f;
constexpr float QSCALE = 0.08838834764831845f;
constexpr unsigned SPIN_LIMIT = 1u << 24;

template <int N>
__device__ __forceinline__ void poll_row16(const unsigned* base, int lane, unsigned tag16, uint2 (&v)[N]) {
    unsigned spins = 0;
    while (true) {
        v[0] = ldg_relaxed2(base + 2 * lane);
        if ((v[0].x & 0xffffu) == tag16 && (v[0].y & 0xffffu) == tag16) break;
        if (++spins > SPIN_LIMIT) TRAP_AT(__LINE__);
        __nanosleep(64);
    }
    bool ok;
    spins = 0;
#pragma unroll
    for (int i = 1; i < N; i++) v[i] = ldg_relaxed2(base + 2 * (lane + 32 * i));
    while (true) {
        ok = true;
#pragma unroll
        for (int i = 1; i < N; i++) {
            if ((v[i].x & 0xffffu) != tag16 || (v[i].y & 0xffffu) != tag16) {
                v[i] = ldg_relaxed2(base + 2 * (lane + 32 * i));
                ok = false;
            }
        }
        if (ok) break;
        if (++spins > SPIN_LIMIT) TRAP_AT(__LINE__);
    }
}

__device__ __forceinline__ void ln_stats(const float (&x)[18], float& mean_r, float& sd_r) {
    float s = 0.f;
#pragma unroll
    for (int i = 0; i < 18; i++) s += x[i];
#pragma unroll
    for (int o = 16; o; o >>= 1) s += __shfl_xor_sync(0xffffffffu, s, o);
    const float mean = s * (1.0f / 576.0f);
    float q = 0.f;
#pragma unroll
    for (int i = 0; i < 18; i++) { float d = x[i] - mean; q += d * d; }
#pragma unroll
    for (int o = 16; o; o >>= 1) q += __shfl_xor_sync(0xffffffffu, q, o);
    const float var = bfr(q * (1.0f / 576.0f));
    mean_r = bfr(mean);
    sd_r = bfr(sqrtf(bfr(var + 1e-5f)));
}
__device__ __forceinline__ float ln_mod(float x, float mean_r, float sd_r, float cmul, float sadd) {
    float y = bfr(bfr(x - mean_r) / sd_r);
    y = bfr(y * bfr(1.0f + cmul));
    return bfr(y + sadd);
}

__global__ void __launch_bounds__(NTHREADS, 1)
fused_kernel(const __grid_constant__ CUtensorMap tmK, const __grid_constant__ CUtensorMap tmV,
             const __grid_constant__ CUtensorMap tmMod, const __grid_constant__ CUtensorMap tmQ,
             const __grid_constant__ CUtensorMap tmO, const __grid_constant__ CUtensorMap tmG,
             const __grid_constant__ CUtensorMap tmU, const __grid_constant__ CUtensorMap tmD,
             const Params prm) {
    extern __shared__ unsigned char smem_raw[];
    const uint32_t sb = (smem_u32(smem_raw) + 1023u) & ~1023u;
    unsigned char* sp = smem_raw + (sb - smem_u32(smem_raw));
    const int tid = threadIdx.x, warp = tid >> 5, lane = tid & 31;
    const int cta = blockIdx.x;
    const uint32_t bar_full = sb + SM_BAR, bar_empty = sb + SM_BAR + 48, bar_ctrl = sb + SM_BAR + 96;
    volatile int2* meta = reinterpret_cast<volatile int2*>(sp + SM_META);
    volatile unsigned* s_epoch = reinterpret_cast<volatile unsigned*>(sp + SM_EPOCH);

    if (warp == 8) {
        if (lane == 0) {
            for (int i = 0; i < NSLOT; i++) { mbar_init(bar_full + 8 * i, 1); mbar_init(bar_empty + 8 * i, 8); }
            for (int i = 0; i < 3; i++) mbar_init(bar_ctrl + 8 * i, 1);
            asm volatile("fence.mbarrier_init.release.cluster;" ::: "memory");
            asm volatile("fence.proxy.async.shared::cta;" ::: "memory");
            if (cta < 108) {
                mbar_expect_tx(bar_full + 0, 36864);
                const int cA = cta < 36 ? 16 * cta : 1152 + 32 * (cta - 36);
                const int cB = cta < 36 ? 576 + 16 * cta : cA + 16;
                for (int i = 0; i < 3; i++) {
                    tma2d(sb + i * 6144, &tmMod, cA, 192 * i, bar_full + 0);
                    tma2d(sb + 18432 + i * 6144, &tmMod, cB, 192 * i, bar_full + 0);
                }
            } else {
                mbar_arrive(bar_full + 0);
            }
            if (cta < NROLE) {
                mbar_expect_tx(bar_full + 8, 36864);
                for (int i = 0; i < 3; i++) tma2d(sb + 36864 + i * 12288, &tmQ, 32 * cta, 192 * i, bar_full + 8);
                for (int u = 0; u < 2; u++) {
                    const int s = 2 + 2 * u;
                    const int row = (cta * SK + u * UKEYS) * 2;
                    mbar_expect_tx(bar_full + 8 * s, SLOT);
                    tma2d(sb + SM_RING + s * SLOT, &tmK, 0, row, bar_full + 8 * s);
                    mbar_expect_tx(bar_full + 8 * (s + 1), SLOT);
                    tma2d(sb + SM_RING + (s + 1) * SLOT, &tmV, 0, row, bar_full + 8 * (s + 1));
                    meta[1 + u].x = cta; meta[1 + u].y = 0;
                    mbar_arrive(bar_ctrl + 8 * (1 + u));
                }
            } else {
                mbar_arrive(bar_full + 8);
            }
        }
        __syncthreads();
        const unsigned epoch = *s_epoch;
        const int par = epoch & 1;
        Ctr* ctr = g_ctr[par];
        int seq = (cta < NROLE) ? 6 : 2;
        int cur = (cta < NROLE) ? cta : -1;
        int pslot = 0;
        bool fresh = false;
        int nunit = 0;
        while (true) {
            const int s = seq % NSLOT;
            const uint32_t ph = ((seq / NSLOT) & 1) ^ 1;
            mbar_wait(bar_empty + 8 * s, ph);
            int unit = -1;
            while (true) {
                if (cur >= 0) {
                    unsigned old = 0;
                    if (lane == 0) old = atomicAdd(&ctr[cur].next, 1u);
                    old = __shfl_sync(0xffffffffu, old, 0) + 2u;
                    if (old < (unsigned)UNITS) { unit = (int)old; break; }
                    cur = -1;
                }
                float best = 0.f; int bestp = -1;
#pragma unroll
                for (int i = 0; i < 4; i++) {
                    const int p = ((lane + 32 * i) + cta * 37) & (NPAIR - 1);
                    uint4 v = ldg_relaxed4(reinterpret_cast<const unsigned*>(&ctr[p]));
                    const int rem = UNITS - 2 - (int)v.z;
                    if (rem > 0) {
                        float sc = (float)rem / (float)(v.x + 1u);
                        if (sc > best) { best = sc; bestp = p; }
                    }
                }
#pragma unroll
                for (int o = 16; o; o >>= 1) {
                    float ob = __shfl_xor_sync(0xffffffffu, best, o);
                    int op = __shfl_xor_sync(0xffffffffu, bestp, o);
                    int ol = lane ^ o;
                    if (ob > best || (ob == best && ol < lane)) { best = ob; bestp = op; }
                }
                bestp = __shfl_sync(0xffffffffu, bestp, 0);
                if (bestp < 0) break;
                cur = bestp; fresh = true;
            }
            const int us = (seq >> 1) % 3;
            if (unit < 0) {
                if (lane == 0) { meta[us].x = -1; mbar_arrive(bar_ctrl + 8 * us); }
                TS(13);
                break;
            }
            if (lane == 0) {
                const int row = (cur * SK + unit * UKEYS) * 2;
                mbar_expect_tx(bar_full + 8 * s, SLOT);
                tma2d(sb + SM_RING + s * SLOT, &tmK, 0, row, bar_full + 8 * s);
                if (fresh) pslot = (int)atomicAdd(&ctr[cur].joined, 1u) + 1;
                meta[us].x = cur; meta[us].y = pslot;
                mbar_arrive(bar_ctrl + 8 * us);
                mbar_wait(bar_empty + 8 * (s + 1), ph);
                mbar_expect_tx(bar_full + 8 * (s + 1), SLOT);
                tma2d(sb + SM_RING + (s + 1) * SLOT, &tmV, 0, row, bar_full + 8 * (s + 1));
            }
            fresh = false;
            seq += 2;
            __syncwarp();
            if (cta == 0 && ++nunit == 8) {
                if (lane == 0) {
                    unsigned spins = 0;
                    while (ldg_relaxed1(&g_started[par]) < gridDim.x) { if (++spins > SPIN_LIMIT) TRAP_AT(__LINE__); }
                    g_started[par ^ 1] = 0;
                    g_epoch = epoch + 1;
                }
#pragma unroll
                for (int i = 0; i < 4; i++)
                    *reinterpret_cast<uint4*>(&g_ctr[par ^ 1][lane + 32 * i]) = make_uint4(0, 0, 0, 0);
            }
        }
        if (cta < NROLE && lane == 0) {
            const int hkv = cta >> 3, ns = cta & 7;
            const int gc = (36 * cta) & ~7;
            for (int i = 0; i < 6; i++) {
                const int sq = seq + i;
                const int s = sq % NSLOT;
                const uint32_t ph = ((sq / NSLOT) & 1) ^ 1;
                const uint32_t dst = sb + SM_RING + s * SLOT;
                const uint32_t fb = bar_full + 8 * s;
                mbar_wait(bar_empty + 8 * s, ph);
                if (i == 0) {
                    mbar_expect_tx(fb, 27648);
                    for (int r = 0; r < 3; r++) tma2d(dst + r * 9216, &tmO, 72 * ns, 256 * hkv + 64 * r, fb);
                } else if (i == 1) {
                    mbar_expect_tx(fb, 9216 + 15360);
                    tma2d(dst, &tmO, 72 * ns, 256 * hkv + 192, fb);
                    tma2d(dst + 9216, &tmG, gc, 0, fb);
                } else if (i == 2) {
                    mbar_expect_tx(fb, 30720);
                    tma2d(dst, &tmU, gc, 0, fb);
                    tma2d(dst + 15360, &tmG, gc, 192, fb);
                } else if (i == 3) {
                    mbar_expect_tx(fb, 30720);
                    tma2d(dst, &tmU, gc, 192, fb);
                    tma2d(dst + 15360, &tmG, gc, 384, fb);
                } else if (i == 4) {
                    mbar_expect_tx(fb, 15360 + 3 * 4608);
                    tma2d(dst, &tmU, gc, 384, fb);
                    for (int r = 0; r < 3; r++) tma2d(dst + 15360 + r * 5120, &tmD, 64 * r, 36 * cta, fb);
                } else {
                    mbar_expect_tx(fb, 6 * 4608);
                    for (int r = 0; r < 6; r++) tma2d(dst + r * 5120, &tmD, 64 * (3 + r), 36 * cta, fb);
                }
            }
        }
        return;
    }

    const int g = lane >> 2, t = lane & 3;
    TS(0);
    if (tid == 0) {
        const unsigned e = ldg_relaxed1(&g_epoch);
        *s_epoch = e;
        atomicAdd(&g_started[e & 1], 1u);
    }
    const uint32_t bufA = sb + SM_BUFA;
    float* s_stat = reinterpret_cast<float*>(sp + SM_STAT);
    if (cta < 108) {
        const unsigned* cw = reinterpret_cast<const unsigned*>(prm.c) + warp * 288;
        unsigned cv[9];
#pragma unroll
        for (int i = 0; i < 9; i++) cv[i] = __ldg(cw + lane + 32 * i);
        if (cta < 36) {
            const unsigned* xw = reinterpret_cast<const unsigned*>(prm.x) + warp * 288;
            float xv[18];
#pragma unroll
            for (int i = 0; i < 9; i++) { unsigned w = __ldg(xw + lane + 32 * i); xv[2 * i] = bf_lo(w); xv[2 * i + 1] = bf_hi(w); }
            float mr, sr;
            ln_stats(xv, mr, sr);
            if (lane == 0) { s_stat[2 * warp] = mr; s_stat[2 * warp + 1] = sr; }
        }
#pragma unroll
        for (int i = 0; i < 9; i++) {
            float a = bf_lo(cv[i]), b = bf_hi(cv[i]);
            a = a / (1.0f + expf(-a));
            b = b / (1.0f + expf(-b));
            *reinterpret_cast<unsigned*>(sp + SM_BUFA + (warp * BUFA_PITCH + 2 * (lane + 32 * i)) * 2) = pack_bf2(a, b);
        }
    }
    __syncthreads();
    const unsigned epoch = *s_epoch;
    const int par = epoch & 1;
    const unsigned tag16 = epoch % 65535u + 1u;
    const unsigned tag2 = epoch % 3u + 1u;
    float4* s_red = reinterpret_cast<float4*>(sp + SM_RED);
    const uint32_t bA = bufA + (g * BUFA_PITCH + 2 * t) * 2;

    if (cta < 108) {
        mbar_wait(bar_full + 0, 0);
        const int tile = warp & 1, kq = warp >> 1;
        float acc[4] = {0.f, 0.f, 0.f, 0.f};
        const int kr = (lane & 7) + 8 * (lane >> 4);
        const uint32_t boxb = sb + ((lane >> 3) & 1) * 18432;
#pragma unroll
        for (int i = 0; i < 9; i++) {
            const int ks = kq * 9 + i;
            const int r = 16 * ks + kr;
            uint32_t a[4];
            ldsm4t(boxb + r * 32 + ((tile ^ ((r >> 2) & 1)) << 4), a);
            const uint32_t b0 = lds32(bA + ks * 32), b1 = lds32(bA + ks * 32 + 16);
            mma16816(acc, a, b0, b1);
        }
        s_red[warp * 32 + lane] = make_float4(acc[0], acc[1], acc[2], acc[3]);
        cons_sync();
        if (warp < 2) {
            float4 v = s_red[warp * 32 + lane];
#pragma unroll
            for (int k = 1; k < 4; k++) { float4 u = s_red[(warp + 2 * k) * 32 + lane]; v.x += u.x; v.y += u.y; v.z += u.z; v.w += u.w; }
            const int cl = 8 * warp + g;
            if (cta < 36) {
                const int col = 16 * cta + cl;
#pragma unroll
                for (int e = 0; e < 2; e++) {
                    const int b = 2 * t + e;
                    const float sa = bfr(e ? v.y : v.x), ca = bfr(e ? v.w : v.z);
                    const float xv = __bfloat162float(prm.x[b * DM + col]);
                    const float h = ln_mod(xv, s_stat[2 * b], s_stat[2 * b + 1], ca, sa);
                    stg_relaxed1(&g_h[b * DM + col], (bf_bits(h) << 16) | tag16);
                }
            } else {
                const int colA = 1152 + 32 * (cta - 36) + cl, colB = colA + 16;
                stg_relaxed1(&g_mod[(2 * t) * 3456 + colA], (bf_bits(v.x) << 16) | tag16);
                stg_relaxed1(&g_mod[(2 * t + 1) * 3456 + colA], (bf_bits(v.y) << 16) | tag16);
                stg_relaxed1(&g_mod[(2 * t) * 3456 + colB], (bf_bits(v.z) << 16) | tag16);
                stg_relaxed1(&g_mod[(2 * t + 1) * 3456 + colB], (bf_bits(v.w) << 16) | tag16);
            }
        }
    }
    TS(1);
    if (cta < NROLE) {
        uint2 hv[9];
        poll_row16<9>(g_h + warp * DM, lane, tag16, hv);
        cons_sync();
#pragma unroll
        for (int i = 0; i < 9; i++)
            *reinterpret_cast<unsigned*>(sp + SM_BUFA + (warp * BUFA_PITCH + 2 * (lane + 32 * i)) * 2) = pack_hi(hv[i].x, hv[i].y);
        cons_sync();
        mbar_wait(bar_full + 8, 0);
        const int tile = warp & 1, kq = warp >> 1;
        float acc[4] = {0.f, 0.f, 0.f, 0.f};
        const int kr = (lane & 7) + 8 * (lane >> 4);
        const int ch = 2 * tile + ((lane >> 3) & 1);
#pragma unroll
        for (int i = 0; i < 9; i++) {
            const int ks = kq * 9 + i;
            const int r = 16 * ks + kr;
            uint32_t a[4];
            ldsm4t(sb + 36864 + r * 64 + ((ch ^ ((r >> 1) & 3)) << 4), a);
            const uint32_t b0 = lds32(bA + ks * 32), b1 = lds32(bA + ks * 32 + 16);
            mma16816(acc, a, b0, b1);
        }
        s_red[warp * 32 + lane] = make_float4(acc[0], acc[1], acc[2], acc[3]);
        cons_sync();
        if (warp < 2) {
            float4 v = s_red[warp * 32 + lane];
#pragma unroll
            for (int k = 1; k < 4; k++) { float4 u = s_red[(warp + 2 * k) * 32 + lane]; v.x += u.x; v.y += u.y; v.z += u.z; v.w += u.w; }
            const int col = 32 * cta + 16 * warp + g;
            stg_relaxed1(&g_q[(2 * t) * 4096 + col], (bf_bits(v.x) << 16) | tag16);
            stg_relaxed1(&g_q[(2 * t + 1) * 4096 + col], (bf_bits(v.y) << 16) | tag16);
            stg_relaxed1(&g_q[(2 * t) * 4096 + col + 8], (bf_bits(v.z) << 16) | tag16);
            stg_relaxed1(&g_q[(2 * t + 1) * 4096 + col + 8], (bf_bits(v.w) << 16) | tag16);
        }
    }
    TS(2);
    __syncwarp();
    if (lane == 0) { mbar_arrive(bar_empty + 0); mbar_arrive(bar_empty + 8); }

    int seq = 2;
    {
        uint32_t kpre[2], vpre[2];
        {
            const int key = (lane & 7) + 8 * ((lane >> 3) & 1), cs = lane >> 4;
#pragma unroll
            for (int h = 0; h < 2; h++) {
                const int r = 2 * (16 * warp + key) + h;
                kpre[h] = r * 128 + ((cs ^ (r & 7)) << 4);
            }
            const int kr = (lane & 7), hi = lane >> 4, cv = (lane >> 3) & 1;
            const int vkey = (kr >> 1) + 8 * (kr & 1) + 4 * hi;
#pragma unroll
            for (int h = 0; h < 2; h++) {
                const int r = 2 * (16 * warp + vkey) + h;
                vpre[h] = r * 128 + ((cv ^ (r & 7)) << 4);
            }
        }
        uint32_t qf[8][2];
        float o[8][4];
        float m = -INFINITY, l = 0.f;
        int cur = -1, pslot = 0, cnt = 0;
        float* scr_o = reinterpret_cast<float*>(sp + SM_SCR);
        float* scr_ml = reinterpret_cast<float*>(sp + SM_ML);
        while (true) {
            const int us = (seq >> 1) % 3;
            const uint32_t cph = (((seq >> 1) - 1) / 3) & 1;
            mbar_wait(bar_ctrl + 8 * us, cph);
            const int np = meta[us].x, nslot = meta[us].y;
            if (np != cur) {
                if (cur >= 0) {
#pragma unroll
                    for (int of = 4; of <= 16; of <<= 1) l += __shfl_xor_sync(0xffffffffu, l, of);
                    if (t == 0) {
#pragma unroll
                        for (int mt = 0; mt < 8; mt++) {
                            scr_o[(warp * 2 + 0) * 128 + 16 * mt + g] = o[mt][0];
                            scr_o[(warp * 2 + 1) * 128 + 16 * mt + g] = o[mt][1];
                            scr_o[(warp * 2 + 0) * 128 + 16 * mt + g + 8] = o[mt][2];
                            scr_o[(warp * 2 + 1) * 128 + 16 * mt + g + 8] = o[mt][3];
                        }
                    }
                    if (lane < 2) { scr_ml[(warp * 2 + lane) * 2] = m; scr_ml[(warp * 2 + lane) * 2 + 1] = l; }
                    cons_sync();
                    {
                        const int h = tid >> 7, d = tid & 127;
                        float M = -INFINITY;
#pragma unroll
                        for (int w = 0; w < 8; w++) M = fmaxf(M, scr_ml[(w * 2 + h) * 2]);
                        float O = 0.f, L = 0.f;
#pragma unroll
                        for (int w = 0; w < 8; w++) {
                            const float f = ex2((scr_ml[(w * 2 + h) * 2] - M) * LOG2E);
                            O += f * scr_o[(w * 2 + h) * 128 + d];
                            L += f * scr_ml[(w * 2 + h) * 2 + 1];
                        }
                        float* rec = g_part + ((size_t)cur * MAXS + pslot) * PSTRIDE;
                        rec[tid] = O;
                        if (d == 0) { rec[256 + 2 * h] = M; rec[257 + 2 * h] = L; }
                    }
                    cons_sync();
                    if (tid == 0) {
                        __threadfence();
                        atomicAdd(&g_ctr[par][cur].done, (unsigned)cnt);
                    }
                }
                if (np < 0) break;
                cur = np; pslot = nslot; cnt = 0;
                m = -INFINITY; l = 0.f;
#pragma unroll
                for (int mt = 0; mt < 8; mt++) { o[mt][0] = o[mt][1] = o[mt][2] = o[mt][3] = 0.f; }
                const unsigned* qb = g_q + (cur >> 4) * 4096 + (cur & 15) * 256 + (g & 1) * 128 + 2 * t;
                unsigned spins = 0;
                while (true) {
                    bool ok = true;
#pragma unroll
                    for (int ks = 0; ks < 8; ks++) {
                        uint2 a = ldg_relaxed2(qb + 16 * ks), b = ldg_relaxed2(qb + 16 * ks + 8);
                        ok = ok && ((a.x & 0xffffu) == tag16) && ((a.y & 0xffffu) == tag16) &&
                             ((b.x & 0xffffu) == tag16) && ((b.y & 0xffffu) == tag16);
                        qf[ks][0] = pack_hi(a.x, a.y);
                        qf[ks][1] = pack_hi(b.x, b.y);
                    }
                    if (__all_sync(0xffffffffu, ok)) break;
                    if (++spins > SPIN_LIMIT) TRAP_AT(__LINE__);
                    __nanosleep(100);
                }
            }
            if (seq == 2) TS(3);
            if (seq == 6) TS(4);
            const int sK = seq % NSLOT;
            const uint32_t ph = (seq / NSLOT) & 1;
            const uint32_t kb = sb + SM_RING + sK * SLOT, vb = kb + SLOT;
            mbar_wait(bar_full + 8 * sK, ph);
            float c0[4] = {0.f, 0.f, 0.f, 0.f}, c1[4] = {0.f, 0.f, 0.f, 0.f};
#pragma unroll
            for (int ks = 0; ks < 8; ks += 2) {
                uint32_t a[4], b[4];
                ldsm4(kb + (kpre[ks >> 2] ^ ((ks & 3) << 5)), a);
                ldsm4(kb + (kpre[(ks + 1) >> 2] ^ (((ks + 1) & 3) << 5)), b);
                mma16816(c0, a, qf[ks][0], qf[ks][1]);
                mma16816(c1, b, qf[ks + 1][0], qf[ks + 1][1]);
            }
            __syncwarp();
            if (lane == 0) mbar_arrive(bar_empty + 8 * sK);
            float s0 = (t & 1) ? (c0[1] + c1[1]) : (c0[0] + c1[0]);
            float s1 = (t & 1) ? (c0[3] + c1[3]) : (c0[2] + c1[2]);
            s0 = bfr(bfr(s0) * QSCALE);
            s1 = bfr(bfr(s1) * QSCALE);
            float bm = fmaxf(s0, s1);
            if (__any_sync(0xffffffffu, bm > m)) {
#pragma unroll
                for (int of = 4; of <= 16; of <<= 1) bm = fmaxf(bm, __shfl_xor_sync(0xffffffffu, bm, of));
                const float mn = fmaxf(m, bm);
                const float al = ex2((m - mn) * LOG2E);
                m = mn; l *= al;
                const float alo = __shfl_xor_sync(0xffffffffu, al, 1);
                const float a0 = (t & 1) ? alo : al, a1 = (t & 1) ? al : alo;
#pragma unroll
                for (int mt = 0; mt < 8; mt++) { o[mt][0] *= a0; o[mt][1] *= a1; o[mt][2] *= a0; o[mt][3] *= a1; }
            }
            const float p0 = ex2((s0 - m) * LOG2E), p1 = ex2((s1 - m) * LOG2E);
            l += p0 + p1;
            const unsigned pk = pack_bf2(p0, p1);
            const unsigned pb0 = __shfl_sync(0xffffffffu, pk, 4 * t + (g & 1));
            const unsigned pb1 = __shfl_sync(0xffffffffu, pk, 4 * (t + 4) + (g & 1));
            mbar_wait(bar_full + 8 * (sK + 1), ph);
#pragma unroll
            for (int mt = 0; mt < 8; mt++) {
                uint32_t a[4];
                ldsm4t(vb + (vpre[mt >> 2] ^ ((mt & 3) << 5)), a);
                mma16816(o[mt], a, pb0, pb1);
            }
            __syncwarp();
            if (lane == 0) mbar_arrive(bar_empty + 8 * (sK + 1));
            cnt++;
            seq += 2;
        }
    }
    TS(5);
    if (tid == 0) TSV(16, seq);
    if (cta >= NROLE) return;

    const int hkv = cta >> 3, ns = cta & 7;
    {
        const int p = warp * HKV + hkv;
        unsigned nj;
        {
            unsigned spins = 0;
            while (true) {
                uint2 v = ldg_relaxed2(reinterpret_cast<const unsigned*>(&g_ctr[par][p]));
                if (v.y == (unsigned)UNITS) { nj = v.x + 1; break; }
                if (++spins > SPIN_LIMIT) TRAP_AT(__LINE__);
                __nanosleep(32);
            }
            __threadfence();
        }
        const int h = lane >> 4;
        const float* rec = g_part + (size_t)p * MAXS * PSTRIDE;
        float M = -INFINITY, L = 0.f;
        float O[8];
#pragma unroll
        for (int i = 0; i < 8; i++) O[i] = 0.f;
        for (unsigned s = 0; s < nj; s++) {
            const float* r = rec + (size_t)s * PSTRIDE;
            const float4 a = __ldcg(reinterpret_cast<const float4*>(r + lane * 8));
            const float4 b = __ldcg(reinterpret_cast<const float4*>(r + lane * 8 + 4));
            const float2 ml = __ldcg(reinterpret_cast<const float2*>(r + 256 + 2 * h));
            const float Mn = fmaxf(M, ml.x);
            const float fo = ex2((M - Mn) * LOG2E), fn = ex2((ml.x - Mn) * LOG2E);
            M = Mn;
            L = L * fo + ml.y * fn;
            O[0] = O[0] * fo + a.x * fn; O[1] = O[1] * fo + a.y * fn; O[2] = O[2] * fo + a.z * fn; O[3] = O[3] * fo + a.w * fn;
            O[4] = O[4] * fo + b.x * fn; O[5] = O[5] * fo + b.y * fn; O[6] = O[6] * fo + b.z * fn; O[7] = O[7] * fo + b.w * fn;
        }
        uint4 w;
        w.x = pack_bf2(O[0] / L, O[1] / L); w.y = pack_bf2(O[2] / L, O[3] / L);
        w.z = pack_bf2(O[4] / L, O[5] / L); w.w = pack_bf2(O[6] / L, O[7] / L);
        *reinterpret_cast<uint4*>(sp + SM_SCR + (warp * BUFO_PITCH + lane * 8) * 2) = w;
    }
    cons_sync();
    TS(6);
    if (warp < 5) {
        const int s0 = seq % NSLOT, s1 = (seq + 1) % NSLOT;
        mbar_wait(bar_full + 8 * s0, (seq / NSLOT) & 1);
        mbar_wait(bar_full + 8 * s1, ((seq + 1) / NSLOT) & 1);
        const uint32_t w0 = sb + SM_RING + s0 * SLOT, w1 = sb + SM_RING + s1 * SLOT;
        const uint32_t bO = sb + SM_SCR + (g * BUFO_PITCH + 2 * t) * 2;
        const int kr = (lane & 7) + 8 * (lane >> 4);
        int cb = 16 * warp + 8 * ((lane >> 3) & 1);
        if (cb > 64) cb = 64;
        float acc[2][4] = {{0.f, 0.f, 0.f, 0.f}, {0.f, 0.f, 0.f, 0.f}};
#pragma unroll
        for (int ks = 0; ks < 16; ks++) {
            const int r = 16 * ks + kr;
            const uint32_t addr = (ks < 12 ? w0 + r * 144 : w1 + (r - 192) * 144) + cb * 2;
            uint32_t a[4];
            ldsm4t(addr, a);
            mma16816(acc[ks & 1], a, lds32(bO + ks * 32), lds32(bO + ks * 32 + 16));
        }
        unsigned* dst = g_wop + (size_t)hkv * (DM * NB) + (72 * ns + 16 * warp + g) * 8 + 2 * t;
        stg_relaxed2(dst, (__float_as_uint(acc[0][0] + acc[1][0]) & ~3u) | tag2, (__float_as_uint(acc[0][1] + acc[1][1]) & ~3u) | tag2);
        if (warp < 4)
            stg_relaxed2(dst + 64, (__float_as_uint(acc[0][2] + acc[1][2]) & ~3u) | tag2, (__float_as_uint(acc[0][3] + acc[1][3]) & ~3u) | tag2);
    }
    TS(7);
    if (warp < 5) {
        const int src = lane & 15, ch = 2 * warp + (lane >> 4);
        if (warp < 4 || lane < 16) {
            const unsigned amask = warp < 4 ? 0xffffffffu : 0x0000ffffu;
            const int v0 = ns * 576 + 36 * hkv + 4 * ch;
            const int vi = v0 + (src & 3);
            const int col = vi >> 3, b = vi & 7;
            float xv = 0.f; unsigned gaw = 0;
            if (src < 4) {
                xv = __bfloat162float(prm.x[b * DM + col]);
                unsigned spins = 0;
                while (((gaw = ldg_relaxed1(&g_mod[b * 3456 + 2 * DM + col])) & 0xffffu) != tag16) { if (++spins > SPIN_LIMIT) TRAP_AT(__LINE__); }
            }
            const unsigned* ptr = g_wop + (size_t)src * (DM * NB) + v0;
            uint4 v;
            unsigned spins = 0;
            while (true) {
                v = ldg_relaxed4(ptr);
                if ((v.x & 3u) == tag2 && (v.y & 3u) == tag2 && (v.z & 3u) == tag2 && (v.w & 3u) == tag2) break;
                if (++spins > SPIN_LIMIT) TRAP_AT(__LINE__);
            }
            float f0 = __uint_as_float(v.x & ~3u), f1 = __uint_as_float(v.y & ~3u), f2 = __uint_as_float(v.z & ~3u), f3 = __uint_as_float(v.w & ~3u);
#pragma unroll
            for (int of = 1; of <= 8; of <<= 1) {
                f0 += __shfl_xor_sync(amask, f0, of); f1 += __shfl_xor_sync(amask, f1, of);
                f2 += __shfl_xor_sync(amask, f2, of); f3 += __shfl_xor_sync(amask, f3, of);
            }
            if (src < 4) {
                const float a = bfr(src == 0 ? f0 : src == 1 ? f1 : src == 2 ? f2 : f3);
                const float x2 = xv + bfr(bf_hi(gaw) * a);
                stg_relaxed1(&g_x2[b * DM + col], (bf_bits(x2) << 16) | tag16);
            }
        }
    }
    TS(8);
    {
        uint2 cbv[9], sbv[9], xv2[9];
        poll_row16<9>(g_mod + warp * 3456 + 4 * DM, lane, tag16, cbv);
        poll_row16<9>(g_mod + warp * 3456 + 3 * DM, lane, tag16, sbv);
        poll_row16<9>(g_x2 + warp * DM, lane, tag16, xv2);
        float xf[18];
#pragma unroll
        for (int i = 0; i < 9; i++) { xf[2 * i] = bf_hi(xv2[i].x); xf[2 * i + 1] = bf_hi(xv2[i].y); }
        float mr, sr;
        ln_stats(xf, mr, sr);
#pragma unroll
        for (int i = 0; i < 9; i++) {
            const float h0 = ln_mod(xf[2 * i], mr, sr, bf_hi(cbv[i].x), bf_hi(sbv[i].x));
            const float h1 = ln_mod(xf[2 * i + 1], mr, sr, bf_hi(cbv[i].y), bf_hi(sbv[i].y));
            *reinterpret_cast<unsigned*>(sp + SM_BUFA + (warp * BUFA_PITCH + 2 * (lane + 32 * i)) * 2) = pack_bf2(h0, h1);
        }
        if (tid < 48) *reinterpret_cast<unsigned*>(sp + SM_ACT + ((tid / 6) * ACT_PITCH + 36 + 2 * (tid % 6)) * 2) = 0;
    }
    cons_sync();
    TS(9);
    if (warp < 5) {
        uint32_t sl[4];
#pragma unroll
        for (int i = 0; i < 4; i++) {
            const int sq = seq + 1 + i;
            mbar_wait(bar_full + 8 * (sq % NSLOT), (sq / NSLOT) & 1);
            sl[i] = sb + SM_RING + (sq % NSLOT) * SLOT;
        }
        const bool isup = (lane >> 3) & 1;
        const int kr = (lane & 7) + 8 * (lane >> 4);
        uint32_t base[3];
        base[0] = isup ? sl[1] : sl[0] + 9216;
        base[1] = isup ? sl[2] : sl[1] + 15360;
        base[2] = isup ? sl[3] : sl[2] + 15360;
        float acc[4][4];
#pragma unroll
        for (int i = 0; i < 4; i++) acc[i][0] = acc[i][1] = acc[i][2] = acc[i][3] = 0.f;
#pragma unroll
        for (int ks = 0; ks < 36; ks++) {
            const int r = (16 * ks) % 192 + kr;
            uint32_t a[4];
            ldsm4t(base[ks / 12] + r * 80 + warp * 16, a);
            mma16816(acc[ks & 3], a, lds32(bA + ks * 32), lds32(bA + ks * 32 + 16));
        }
        const int cl = 8 * warp + g - 4 * (cta & 1);
#pragma unroll
        for (int e = 0; e < 2; e++) {
            const float gt = bfr(acc[0][e] + acc[1][e] + acc[2][e] + acc[3][e]);
            const float up = bfr(acc[0][2 + e] + acc[1][2 + e] + acc[2][2 + e] + acc[3][2 + e]);
            const float inner = 0.7978845608028654f * (gt + 0.044715f * gt * gt * gt);
            const float ge = bfr(0.5f * gt * (1.0f + tanhf(inner)));
            if (cl >= 0 && cl < 36)
                *reinterpret_cast<__nv_bfloat16*>(sp + SM_ACT + ((2 * t + e) * ACT_PITCH + cl) * 2) = __float2bfloat16_rn(ge * up);
        }
    }
    cons_sync();
    TS(10);
    {
        const int s4 = (seq + 4) % NSLOT, s5 = (seq + 5) % NSLOT;
        mbar_wait(bar_full + 8 * s4, ((seq + 4) / NSLOT) & 1);
        mbar_wait(bar_full + 8 * s5, ((seq + 5) / NSLOT) & 1);
        const uint32_t d4 = sb + SM_RING + s4 * SLOT + 15360, d5 = sb + SM_RING + s5 * SLOT;
        const uint32_t bAct = sb + SM_ACT + (g * ACT_PITCH + 2 * t) * 2;
        uint32_t bf[3][2];
#pragma unroll
        for (int ks = 0; ks < 3; ks++) { bf[ks][0] = lds32(bAct + ks * 32); bf[ks][1] = lds32(bAct + ks * 32 + 16); }
        const int kr = (lane & 7) + 8 * (lane >> 4), cs = (lane >> 3) & 1;
        for (int tile = warp; tile < 36; tile += 8) {
            const int cbk = tile >> 2;
            const uint32_t box = cbk < 3 ? d4 + cbk * 5120 : d5 + (cbk - 3) * 5120;
            const int ch = (tile & 3) * 2 + cs;
            float acc[4] = {0.f, 0.f, 0.f, 0.f};
#pragma unroll
            for (int ks = 0; ks < 3; ks++) {
                int r = 16 * ks + kr;
                if (r > 35) r = 35;
                uint32_t a[4];
                ldsm4t(box + r * 128 + ((ch ^ (r & 7)) << 4), a);
                mma16816(acc, a, bf[ks][0], bf[ks][1]);
            }
            unsigned* dst = g_dnp + (size_t)cta * (DM * NB) + (16 * tile + g) * 8 + 2 * t;
            stg_relaxed2(dst, (__float_as_uint(acc[0]) & ~3u) | tag2, (__float_as_uint(acc[1]) & ~3u) | tag2);
            stg_relaxed2(dst + 64, (__float_as_uint(acc[2]) & ~3u) | tag2, (__float_as_uint(acc[3]) & ~3u) | tag2);
        }
    }
    TS(11);
    if (cta < 72) {
        unsigned x2w = 0, gbw = 0;
        if (tid < 64) {
            const int col = 8 * cta + (tid >> 3), b = tid & 7;
            x2w = ldg_relaxed1(&g_x2[b * DM + col]);
            unsigned spins = 0;
            while (((gbw = ldg_relaxed1(&g_mod[b * 3456 + 5 * DM + col])) & 0xffffu) != tag16) { if (++spins > SPIN_LIMIT) TRAP_AT(__LINE__); }
        }
        const int ch = lane & 15, sl = lane >> 4;
        const unsigned* ptr = g_dnp + (size_t)(16 * warp + sl) * (DM * NB) + 64 * cta + 4 * ch;
        uint4 v[8];
#pragma unroll
        for (int i = 0; i < 8; i++) v[i] = ldg_relaxed4(ptr + (size_t)(2 * i) * (DM * NB));
        unsigned spins = 0;
        while (true) {
            bool ok = true;
#pragma unroll
            for (int i = 0; i < 8; i++) {
                if ((v[i].x & 3u) != tag2 || (v[i].y & 3u) != tag2 || (v[i].z & 3u) != tag2 || (v[i].w & 3u) != tag2) {
                    v[i] = ldg_relaxed4(ptr + (size_t)(2 * i) * (DM * NB));
                    ok = false;
                }
            }
            if (ok) break;
            if (++spins > SPIN_LIMIT) TRAP_AT(__LINE__);
        }
        float f[4] = {0.f, 0.f, 0.f, 0.f};
#pragma unroll
        for (int i = 0; i < 8; i++) {
            f[0] += __uint_as_float(v[i].x & ~3u); f[1] += __uint_as_float(v[i].y & ~3u);
            f[2] += __uint_as_float(v[i].z & ~3u); f[3] += __uint_as_float(v[i].w & ~3u);
        }
#pragma unroll
        for (int e = 0; e < 4; e++) f[e] += __shfl_xor_sync(0xffffffffu, f[e], 16);
        if (lane < 16) s_red[warp * 16 + ch] = make_float4(f[0], f[1], f[2], f[3]);
        cons_sync();
        if (tid < 64) {
            const float* r = reinterpret_cast<const float*>(s_red);
            float s = 0.f;
#pragma unroll
            for (int w = 0; w < 8; w++) s += r[w * 64 + tid];
            const float o = bf_hi(x2w) + bfr(bf_hi(gbw) * bfr(s));
            prm.out[(tid & 7) * DM + 8 * cta + (tid >> 3)] = __float2bfloat16_rn(o);
        }
        TS(12);
    }
}

typedef CUresult (*EncodeFn)(CUtensorMap*, CUtensorMapDataType, cuuint32_t, void*, const cuuint64_t*, const cuuint64_t*,
                             const cuuint32_t*, const cuuint32_t*, CUtensorMapInterleave, CUtensorMapSwizzle,
                             CUtensorMapL2promotion, CUtensorMapFloatOOBfill);

bool make_map(EncodeFn fn, CUtensorMap* m, const void* ptr, uint64_t inner, uint64_t outer, uint64_t stride_bytes,
              uint32_t box_inner, uint32_t box_outer, CUtensorMapSwizzle sw, CUtensorMapL2promotion promo) {
    cuuint64_t dims[2] = {inner, outer};
    cuuint64_t strides[1] = {stride_bytes};
    cuuint32_t box[2] = {box_inner, box_outer};
    cuuint32_t es[2] = {1, 1};
    return fn(m, CU_TENSOR_MAP_DATA_TYPE_BFLOAT16, 2, const_cast<void*>(ptr), dims, strides, box, es,
              CU_TENSOR_MAP_INTERLEAVE_NONE, sw, promo, CU_TENSOR_MAP_FLOAT_OOB_FILL_NONE) == CUDA_SUCCESS;
}

}

extern "C" void kernel_launch(void* const* d_in, const int* in_sizes, int n_in, void* d_out, int out_size) {
    (void)in_sizes; (void)n_in; (void)out_size;
    static EncodeFn encode = nullptr;
    static int num_sms = 0;
    if (!encode) {
        void* fn = nullptr;
        cudaDriverEntryPointQueryResult qres;
        cudaGetDriverEntryPoint("cuTensorMapEncodeTiled", &fn, cudaEnableDefault, &qres);
        encode = (EncodeFn)fn;
        int dev = 0;
        cudaGetDevice(&dev);
        cudaDeviceGetAttribute(&num_sms, cudaDevAttrMultiProcessorCount, dev);
        cudaFuncSetAttribute(fused_kernel, cudaFuncAttributeMaxDynamicSharedMemorySize, SMEM_BYTES);
    }
    CUtensorMap tmK, tmV, tmMod, tmQ, tmO, tmG, tmU, tmD;
    const uint64_t kvrows = (uint64_t)NB * HKV * SK * 2;
    make_map(encode, &tmK, d_in[1], 64, kvrows, 128, 64, 256, CU_TENSOR_MAP_SWIZZLE_128B, CU_TENSOR_MAP_L2_PROMOTION_L2_256B);
    make_map(encode, &tmV, d_in[2], 64, kvrows, 128, 64, 256, CU_TENSOR_MAP_SWIZZLE_128B, CU_TENSOR_MAP_L2_PROMOTION_L2_256B);
    make_map(encode, &tmQ, d_in[3], 4096, DM, 8192, 32, 192, CU_TENSOR_MAP_SWIZZLE_64B, CU_TENSOR_MAP_L2_PROMOTION_L2_128B);
    make_map(encode, &tmO, d_in[4], DM, 4096, DM * 2, 72, 64, CU_TENSOR_MAP_SWIZZLE_NONE, CU_TENSOR_MAP_L2_PROMOTION_L2_128B);
    make_map(encode, &tmG, d_in[6], FF, DM, FF * 2, 40, 192, CU_TENSOR_MAP_SWIZZLE_NONE, CU_TENSOR_MAP_L2_PROMOTION_L2_128B);
    make_map(encode, &tmU, d_in[7], FF, DM, FF * 2, 40, 192, CU_TENSOR_MAP_SWIZZLE_NONE, CU_TENSOR_MAP_L2_PROMOTION_L2_128B);
    make_map(encode, &tmD, d_in[8], DM, FF, DM * 2, 64, 36, CU_TENSOR_MAP_SWIZZLE_128B, CU_TENSOR_MAP_L2_PROMOTION_L2_128B);
    make_map(encode, &tmMod, d_in[10], 6 * DM, DM, 6 * DM * 2, 16, 192, CU_TENSOR_MAP_SWIZZLE_32B, CU_TENSOR_MAP_L2_PROMOTION_L2_128B);
    Params prm;
    prm.x = (const __nv_bfloat16*)d_in[0];
    prm.c = (const __nv_bfloat16*)d_in[9];
    prm.out = (__nv_bfloat16*)d_out;
    int grid = num_sms < MAXCTA ? num_sms : MAXCTA;
    fused_kernel<<<grid, NTHREADS, SMEM_BYTES>>>(tmK, tmV, tmMod, tmQ, tmO, tmG, tmU, tmD, prm);
}
```

```cpp
#include <cuda_runtime.h>
#include <cuda_bf16.h>
#include <cuda.h>
#include <stdint.h>

namespace {

constexpr int NB = 8;
constexpr int DM = 576;
constexpr int HKV = 16;
constexpr int SK = 8192;
constexpr int DH = 128;
constexpr int FF = 4608;
constexpr int NPAIR = NB * HKV;
constexpr int UKEYS = 128;
constexpr int UNITS = SK / UKEYS;
constexpr int SLOT = 32768;
constexpr int NSLOT = 6;
constexpr int NROLE = 128;
constexpr int MAXCTA = 132;
constexpr int MAXS = MAXCTA + 1;
constexpr int PSTRIDE = 264;
constexpr int NCONS = 256;
constexpr int NTHREADS = 288;

constexpr int SM_SCR = 0;
constexpr int SM_RING = 8192;
constexpr int SM_BUFA = SM_RING + NSLOT * SLOT;
constexpr int BUFA_PITCH = 584;
constexpr int SM_RED = SM_BUFA + 8 * BUFA_PITCH * 2;
constexpr int SM_ACT = SM_RED + 4096;
constexpr int ACT_PITCH = 56;
constexpr int SM_ML = SM_ACT + 8 * ACT_PITCH * 2;
constexpr int SM_STAT = SM_ML + 128;
constexpr int SM_META = SM_STAT + 64;
constexpr int SM_BAR = SM_META + 32;
constexpr int SM_EPOCH = SM_BAR + 16 * 8;
constexpr int SM_NJ = SM_EPOCH + 16;
constexpr int SM_TOTAL = SM_NJ + 128;
constexpr int SMEM_BYTES = SM_TOTAL + 1024;
constexpr int BUFO_PITCH = 264;

__device__ __align__(16) unsigned g_ctr[2][NPAIR];
__device__ unsigned g_epoch;
__device__ unsigned g_started[2];
__device__ __align__(16) unsigned g_h[NB * DM];
__device__ __align__(16) unsigned g_mod[NB * 6 * DM];
__device__ __align__(16) unsigned g_q[NB * 4096];
__device__ __align__(16) unsigned long long g_part[(size_t)NPAIR * MAXS * PSTRIDE];
__device__ __align__(16) unsigned g_wop[HKV * DM * NB];
__device__ __align__(16) unsigned g_x2[NB * DM];
__device__ __align__(16) unsigned g_dnp[(size_t)NROLE * DM * NB];

struct Params {
    const __nv_bfloat16* x;
    const __nv_bfloat16* c;
    const unsigned char* wt[4];
    __nv_bfloat16* out;
};

#define TRAP_AT(line) __trap()
#define TS(i)
#define TSV(i, v)

__device__ __forceinline__ uint32_t smem_u32(const void* p) { return (uint32_t)__cvta_generic_to_shared(p); }
__device__ __forceinline__ void mbar_init(uint32_t bar, uint32_t cnt) {
    asm volatile("mbarrier.init.shared::cta.b64 [%0], %1;" ::"r"(bar), "r"(cnt) : "memory");
}
__device__ __forceinline__ void mbar_expect_tx(uint32_t bar, uint32_t bytes) {
    asm volatile("mbarrier.arrive.expect_tx.shared::cta.b64 _, [%0], %1;" ::"r"(bar), "r"(bytes) : "memory");
}
__device__ __forceinline__ void mbar_arrive(uint32_t bar) {
    asm volatile("mbarrier.arrive.shared::cta.b64 _, [%0];" ::"r"(bar) : "memory");
}
__device__ __forceinline__ bool mbar_try(uint32_t bar, uint32_t parity) {
    uint32_t ok;
    asm volatile(
        "{\n.reg .pred p;\n"
        "mbarrier.try_wait.parity.shared::cta.b64 p, [%1], %2;\n"
        "selp.u32 %0, 1, 0, p;\n}\n"
        : "=r"(ok) : "r"(bar), "r"(parity) : "memory");
    return ok != 0;
}
__device__ __forceinline__ void mbar_wait(uint32_t bar, uint32_t parity) {
    unsigned spins = 0;
    while (!mbar_try(bar, parity)) {
        if (++spins > (1u << 26)) TRAP_AT(__LINE__);
    }
}
__device__ __forceinline__ void tma2d(uint32_t dst, const CUtensorMap* map, int c0, int c1, uint32_t bar) {
    asm volatile(
        "cp.async.bulk.tensor.2d.shared::cluster.global.mbarrier::complete_tx::bytes [%0], [%1, {%3, %4}], [%2];"
        ::"r"(dst), "l"((uint64_t)map), "r"(bar), "r"(c0), "r"(c1) : "memory");
}
__device__ __forceinline__ void tma2d_hint(uint32_t dst, const CUtensorMap* map, int c0, int c1, uint32_t bar, uint64_t pol) {
    asm volatile(
        "cp.async.bulk.tensor.2d.shared::cluster.global.mbarrier::complete_tx::bytes.L2::cache_hint [%0], [%1, {%3, %4}], [%2], %5;"
        ::"r"(dst), "l"((uint64_t)map), "r"(bar), "r"(c0), "r"(c1), "l"(pol) : "memory");
}
__device__ __forceinline__ void l2_prefetch(const void* p, uint32_t bytes) {
    asm volatile("cp.async.bulk.prefetch.L2.global [%0], %1;" ::"l"(p), "r"(bytes) : "memory");
}
__device__ __forceinline__ void ldsm4(uint32_t addr, uint32_t (&r)[4]) {
    asm volatile("ldmatrix.sync.aligned.m8n8.x4.shared.b16 {%0,%1,%2,%3}, [%4];"
                 : "=r"(r[0]), "=r"(r[1]), "=r"(r[2]), "=r"(r[3]) : "r"(addr) : "memory");
}
__device__ __forceinline__ void ldsm4t(uint32_t addr, uint32_t (&r)[4]) {
    asm volatile("ldmatrix.sync.aligned.m8n8.x4.trans.shared.b16 {%0,%1,%2,%3}, [%4];"
                 : "=r"(r[0]), "=r"(r[1]), "=r"(r[2]), "=r"(r[3]) : "r"(addr) : "memory");
}
__device__ __forceinline__ void mma16816(float (&c)[4], const uint32_t (&a)[4], uint32_t b0, uint32_t b1) {
    asm volatile(
        "mma.sync.aligned.m16n8k16.row.col.f32.bf16.bf16.f32 {%0,%1,%2,%3}, {%4,%5,%6,%7}, {%8,%9}, {%0,%1,%2,%3};"
        : "+f"(c[0]), "+f"(c[1]), "+f"(c[2]), "+f"(c[3])
        : "r"(a[0]), "r"(a[1]), "r"(a[2]), "r"(a[3]), "r"(b0), "r"(b1));
}
__device__ __forceinline__ void cons_sync() { asm volatile("bar.sync 1, 256;" ::: "memory"); }
__device__ __forceinline__ uint32_t lds32(uint32_t addr) {
    uint32_t v; asm volatile("ld.shared.u32 %0, [%1];" : "=r"(v) : "r"(addr) : "memory"); return v;
}
__device__ __forceinline__ uint2 ldg_relaxed2(const unsigned* p) {
    uint2 v; asm volatile("ld.relaxed.gpu.global.v2.u32 {%0,%1}, [%2];" : "=r"(v.x), "=r"(v.y) : "l"(p) : "memory"); return v;
}
__device__ __forceinline__ uint4 ldg_relaxed4(const unsigned* p) {
    uint4 v; asm volatile("ld.relaxed.gpu.global.v4.u32 {%0,%1,%2,%3}, [%4];"
                          : "=r"(v.x), "=r"(v.y), "=r"(v.z), "=r"(v.w) : "l"(p) : "memory"); return v;
}
__device__ __forceinline__ unsigned ldg_relaxed1(const unsigned* p) {
    unsigned v; asm volatile("ld.relaxed.gpu.global.u32 %0, [%1];" : "=r"(v) : "l"(p) : "memory"); return v;
}
__device__ __forceinline__ void stg_relaxed1(unsigned* p, unsigned v) {
    asm volatile("st.relaxed.gpu.global.u32 [%0], %1;" ::"l"(p), "r"(v) : "memory");
}
__device__ __forceinline__ void stg_relaxed2(unsigned* p, unsigned a, unsigned b) {
    asm volatile("st.relaxed.gpu.global.v2.u32 [%0], {%1,%2};" ::"l"(p), "r"(a), "r"(b) : "memory");
}
__device__ __forceinline__ ulonglong2 ldg_relaxed2x64(const unsigned long long* p) {
    ulonglong2 v; asm volatile("ld.relaxed.gpu.global.v2.b64 {%0,%1}, [%2];" : "=l"(v.x), "=l"(v.y) : "l"(p) : "memory"); return v;
}
__device__ __forceinline__ void stg_relaxed64(unsigned long long* p, unsigned lo, unsigned hi) {
    asm volatile("{\n.reg .b64 v;\nmov.b64 v, {%1,%2};\nst.relaxed.gpu.global.b64 [%0], v;\n}\n" ::"l"(p), "r"(lo), "r"(hi) : "memory");
}
__device__ __forceinline__ float ex2(float x) { float y; asm("ex2.approx.ftz.f32 %0, %1;" : "=f"(y) : "f"(x)); return y; }

__device__ __forceinline__ float bfr(float x) { return __bfloat162float(__float2bfloat16_rn(x)); }
__device__ __forceinline__ unsigned bf_bits(float x) { return (unsigned)__bfloat16_as_ushort(__float2bfloat16_rn(x)); }
__device__ __forceinline__ float bf_hi(unsigned w) { return __uint_as_float(w & 0xffff0000u); }
__device__ __forceinline__ float bf_lo(unsigned w) { return __uint_as_float(w << 16); }
__device__ __forceinline__ unsigned pack_hi(unsigned lo_word, unsigned hi_word) {
    return __byte_perm(lo_word, hi_word, 0x7632);
}
__device__ __forceinline__ unsigned pack_bf2(float lo, float hi) {
    unsigned r; asm("cvt.rn.bf16x2.f32 %0, %1, %2;" : "=r"(r) : "f"(hi), "f"(lo)); return r;
}
constexpr float LOG2E = 1.4426950408889634f;
constexpr float QSCALE = 0.08838834764831845f;
constexpr unsigned SPIN_LIMIT = 1u << 24;

#define KV_START 1
#define TAILW_MODE 1
#define KV_EF 1
#define WPF_AT 40
#define PF_MIN 6

__device__ __forceinline__ void issue_row16(const unsigned* base, int lane, uint2 (&v)[9]) {
#pragma unroll
    for (int i = 0; i < 9; i++) v[i] = ldg_relaxed2(base + 2 * (lane + 32 * i));
}
__device__ __forceinline__ void check_row16(const unsigned* base, int lane, unsigned tag16, uint2 (&v)[9]) {
    unsigned spins = 0;
    while (true) {
        bool ok = true;
#pragma unroll
        for (int i = 0; i < 9; i++) {
            if ((v[i].x & 0xffffu) != tag16 || (v[i].y & 0xffffu) != tag16) {
                v[i] = ldg_relaxed2(base + 2 * (lane + 32 * i));
                ok = false;
            }
        }
        if (ok) break;
        if (++spins > SPIN_LIMIT) TRAP_AT(__LINE__);
    }
}

__device__ __forceinline__ void ln_stats(const float (&x)[18], float& mean_r, float& rs) {
    float s = 0.f;
#pragma unroll
    for (int i = 0; i < 18; i++) s += x[i];
#pragma unroll
    for (int o = 16; o; o >>= 1) s += __shfl_xor_sync(0xffffffffu, s, o);
    const float mean = s * (1.0f / 576.0f);
    float q = 0.f;
#pragma unroll
    for (int i = 0; i < 18; i++) { float d = x[i] - mean; q += d * d; }
#pragma unroll
    for (int o = 16; o; o >>= 1) q += __shfl_xor_sync(0xffffffffu, q, o);
    const float var = bfr(q * (1.0f / 576.0f));
    mean_r = bfr(mean);
    rs = __frcp_rn(bfr(sqrtf(bfr(var + 1e-5f))));
}
__device__ __forceinline__ float ln_mod(float x, float mean_r, float rs, float cmul, float sadd) {
    float y = bfr(bfr(x - mean_r) * rs);
    y = bfr(y * bfr(1.0f + cmul));
    return bfr(y + sadd);
}
__device__ __forceinline__ float silu_f(float a) { return __fdividef(a, 1.0f + __expf(-a)); }

__global__ void __launch_bounds__(NTHREADS, 1)
fused_kernel(const __grid_constant__ CUtensorMap tmK, const __grid_constant__ CUtensorMap tmV,
             const __grid_constant__ CUtensorMap tmMod, const __grid_constant__ CUtensorMap tmQ,
             const __grid_constant__ CUtensorMap tmO, const __grid_constant__ CUtensorMap tmG,
             const __grid_constant__ CUtensorMap tmU, const __grid_constant__ CUtensorMap tmD,
             const Params prm) {
    extern __shared__ unsigned char smem_raw[];
    const uint32_t sb = (smem_u32(smem_raw) + 1023u) & ~1023u;
    unsigned char* sp = smem_raw + (sb - smem_u32(smem_raw));
    const int tid = threadIdx.x, warp = tid >> 5, lane = tid & 31;
    const int cta = blockIdx.x;
    const uint32_t bar_full = sb + SM_BAR, bar_empty = sb + SM_BAR + 48, bar_ctrl = sb + SM_BAR + 96;
    const uint32_t bar_sig = sb + SM_BAR + 120;
    volatile int2* meta = reinterpret_cast<volatile int2*>(sp + SM_META);
    volatile unsigned* s_epoch = reinterpret_cast<volatile unsigned*>(sp + SM_EPOCH);

    if (warp == 8) {
        uint64_t pol_ef;
        asm volatile("createpolicy.fractional.L2::evict_first.b64 %0, 1.0;" : "=l"(pol_ef));
        if (lane == 0) {
            for (int i = 0; i < NSLOT; i++) { mbar_init(bar_full + 8 * i, 1); mbar_init(bar_empty + 8 * i, 8); }
            for (int i = 0; i < 4; i++) mbar_init(bar_ctrl + 8 * i, 1);
            asm volatile("fence.mbarrier_init.release.cluster;" ::: "memory");
            asm volatile("fence.proxy.async.shared::cta;" ::: "memory");
            if (cta < 36) {
                mbar_expect_tx(bar_full + 0, 36864);
                for (int i = 0; i < 3; i++) {
                    tma2d(sb + i * 6144, &tmMod, 16 * cta, 192 * i, bar_full + 0);
                    tma2d(sb + 18432 + i * 6144, &tmMod, 576 + 16 * cta, 192 * i, bar_full + 0);
                }
            }
        }
        __syncthreads();
        if (lane == 0) {
            if (cta < NROLE) {
                mbar_expect_tx(bar_full + 8, 36864);
                for (int i = 0; i < 3; i++) tma2d(sb + 36864 + i * 12288, &tmQ, 32 * cta, 192 * i, bar_full + 8);
            } else {
                mbar_arrive(bar_full + 8);
            }
            if (cta >= 36 && cta < 108) {
                mbar_expect_tx(bar_full + 0, 36864);
                const int cA = 1152 + 32 * (cta - 36);
                for (int i = 0; i < 3; i++) {
                    tma2d(sb + i * 6144, &tmMod, cA, 192 * i, bar_full + 0);
                    tma2d(sb + 18432 + i * 6144, &tmMod, cA + 16, 192 * i, bar_full + 0);
                }
            } else if (cta >= 108) {
                mbar_arrive(bar_full + 0);
            }
#define TMA_KV(dst, map, row, bar) tma2d_hint(dst, map, 0, row, bar, pol_ef)
            if (cta < NROLE) {
                mbar_wait(bar_full + 0, 0);
                mbar_wait(bar_full + 8, 0);
                for (int u = 0; u < 2; u++) {
                    const int s = 2 + 2 * u;
                    const int row = (cta * SK + u * UKEYS) * 2;
                    mbar_expect_tx(bar_full + 8 * s, SLOT);
                    TMA_KV(sb + SM_RING + s * SLOT, &tmK, row, bar_full + 8 * s);
                    mbar_expect_tx(bar_full + 8 * (s + 1), SLOT);
                    TMA_KV(sb + SM_RING + (s + 1) * SLOT, &tmV, row, bar_full + 8 * (s + 1));
                    meta[1 + u].x = cta; meta[1 + u].y = 0;
                    mbar_arrive(bar_ctrl + 8 * (1 + u));
                }
            }
        }
        __syncwarp();
        int seq = (cta < NROLE) ? 6 : 2;
        if (cta >= NROLE) mbar_wait(bar_empty + 0, 0);
        else mbar_wait(bar_empty + 0, 0);
        const unsigned epoch = *s_epoch;
        const int par = epoch & 1;
        const unsigned tag32 = epoch + 1u;
        unsigned* ctr = g_ctr[par];
        int cur = (cta < NROLE) ? cta : -1;
        int pslot = 0;
        bool have = false;
        unsigned pf = 0;
        int nunit = 0;
        int wpf = 0;
        auto wprefetch = [&](int i) {
            const unsigned half = (i < 2) ? 18432u : 20736u;
            l2_prefetch(prm.wt[i >> 1] + (size_t)(2 * cta + (i & 1)) * half, half);
        };
        uint4 scan = make_uint4(0, 0, 0, 0);
        while (true) {
            const int s = seq % NSLOT;
            const uint32_t ph = ((seq / NSLOT) & 1) ^ 1;
            mbar_wait(bar_empty + 8 * s, ph);
            int unit = -1;
            while (true) {
                bool fresh = false;
                if (cur < 0) {
                    scan = ldg_relaxed4(ctr + 4 * lane);
                    float best = 0.f; int bestp = -1;
                    const unsigned sv[4] = {scan.x, scan.y, scan.z, scan.w};
#pragma unroll
                    for (int i = 0; i < 4; i++) {
                        const int rem = UNITS - 2 - (int)(sv[i] & 0xffffu);
                        if (rem > 0) {
                            const int p = 4 * lane + i;
                            const float sc = __fdividef((float)rem, (float)((sv[i] >> 16) + 1u)) + 0.001f * (float)((p + cta * 37) & 127);
                            if (sc > best) { best = sc; bestp = p; }
                        }
                    }
#pragma unroll
                    for (int o = 16; o; o >>= 1) {
                        const float ob = __shfl_xor_sync(0xffffffffu, best, o);
                        const int op = __shfl_xor_sync(0xffffffffu, bestp, o);
                        if (ob > best || (ob == best && op > bestp)) { best = ob; bestp = op; }
                    }
                    if (bestp < 0) break;
                    cur = bestp; fresh = true;
                }
                unsigned old = pf;
                if (!have) {
                    if (lane == 0) old = atomicAdd(&ctr[cur], fresh ? 0x10001u : 1u);
                }
                have = false;
                old = __shfl_sync(0xffffffffu, old, 0);
                if (fresh) pslot = (int)(old >> 16) + 1;
                const int tk = (int)(old & 0xffffu) + 2;
                if (tk < UNITS) { unit = tk; break; }
                if (fresh) {
                    unsigned long long* rec = g_part + ((size_t)cur * MAXS + pslot) * PSTRIDE;
                    for (int i = lane; i < 260; i += 32)
                        stg_relaxed64(rec + i, (i == 256 || i == 258) ? 0xff800000u : 0u, tag32);
                }
                cur = -1;
            }
            const int us = (seq >> 1) % 3;
            if (unit < 0) {
                *reinterpret_cast<unsigned*>(sp + SM_NJ + 4 * lane) =
                    (scan.x >> 16) | ((scan.y >> 16) << 8) | ((scan.z >> 16) << 16) | ((scan.w >> 16) << 24);
                __syncwarp();
                if (lane == 0) { meta[us].x = -1; mbar_arrive(bar_ctrl + 8 * us); }
                TS(13);
                break;
            }
            if (lane == 0) {
                const int row = (cur * SK + unit * UKEYS) * 2;
                mbar_expect_tx(bar_full + 8 * s, SLOT);
                TMA_KV(sb + SM_RING + s * SLOT, &tmK, row, bar_full + 8 * s);
                meta[us].x = cur; meta[us].y = pslot;
                mbar_arrive(bar_ctrl + 8 * us);
                if (UNITS - unit > PF_MIN) pf = atomicAdd(&ctr[cur], 1u);
                mbar_wait(bar_empty + 8 * (s + 1), ph);
                mbar_expect_tx(bar_full + 8 * (s + 1), SLOT);
                TMA_KV(sb + SM_RING + (s + 1) * SLOT, &tmV, row, bar_full + 8 * (s + 1));
                if (nunit >= WPF_AT && wpf < 8 && cta < NROLE) { wprefetch(wpf); wpf++; }
            }
            have = (UNITS - unit > PF_MIN);
            seq += 2;
            __syncwarp();
            ++nunit;
            if (cta == 0 && nunit == 8) {
                if (lane == 0) {
                    unsigned spins = 0;
                    while (ldg_relaxed1(&g_started[par]) < gridDim.x) { if (++spins > SPIN_LIMIT) TRAP_AT(__LINE__); }
                    g_started[par ^ 1] = 0;
                    g_epoch = epoch + 1;
                }
                *reinterpret_cast<uint4*>(&g_ctr[par ^ 1][4 * lane]) = make_uint4(0, 0, 0, 0);
            }
        }
        if (cta < NROLE && lane == 0) {
            for (; wpf < 8; wpf++) wprefetch(wpf);
            const int hkv = cta >> 3, ns = cta & 7;
            const int gc = (36 * cta) & ~7;
            for (int i = 0; i < 6; i++) {
                const int sq = seq + i;
                const int s = sq % NSLOT;
                const uint32_t ph = ((sq / NSLOT) & 1) ^ 1;
                const uint32_t dst = sb + SM_RING + s * SLOT;
                const uint32_t fb = bar_full + 8 * s;
                mbar_wait(bar_empty + 8 * s, ph);
                if (i == 0) {
                    mbar_expect_tx(fb, 27648);
                    for (int r = 0; r < 3; r++) tma2d(dst + r * 9216, &tmO, 72 * ns, 256 * hkv + 64 * r, fb);
                } else if (i == 1) {
                    mbar_expect_tx(fb, 9216 + 15360);
                    tma2d(dst, &tmO, 72 * ns, 256 * hkv + 192, fb);
                    mbar_wait(bar_sig, KV_START == 2 ? 1 : 0);
                    tma2d(dst + 9216, &tmG, gc, 0, fb);
                } else if (i == 2) {
                    mbar_expect_tx(fb, 30720);
                    tma2d(dst, &tmU, gc, 0, fb);
                    tma2d(dst + 15360, &tmG, gc, 192, fb);
                } else if (i == 3) {
                    mbar_expect_tx(fb, 30720);
                    tma2d(dst, &tmU, gc, 192, fb);
                    tma2d(dst + 15360, &tmG, gc, 384, fb);
                } else if (i == 4) {
                    mbar_expect_tx(fb, 15360 + 3 * 4608);
                    tma2d(dst, &tmU, gc, 384, fb);
                    for (int r = 0; r < 3; r++) tma2d(dst + 15360 + r * 5120, &tmD, 64 * r, 36 * cta, fb);
                } else {
                    mbar_expect_tx(fb, 6 * 4608);
                    for (int r = 0; r < 6; r++) tma2d(dst + r * 5120, &tmD, 64 * (3 + r), 36 * cta, fb);
                }
            }
        }
        return;
    }

    const int g = lane >> 2, t = lane & 3;
    TS(0);
    unsigned e0 = 0;
    if (tid == 0) e0 = ldg_relaxed1(&g_epoch);
    const uint32_t bufA = sb + SM_BUFA;
    float* s_stat = reinterpret_cast<float*>(sp + SM_STAT);
    unsigned* bufArow = reinterpret_cast<unsigned*>(sp + SM_BUFA + warp * BUFA_PITCH * 2) + lane;
    unsigned cv[9];
    float xh[2] = {0.f, 0.f};
    if (cta < 108) {
        const unsigned* cw = reinterpret_cast<const unsigned*>(prm.c) + warp * 288;
#pragma unroll
        for (int i = 0; i < 9; i++) cv[i] = __ldg(cw + lane + 32 * i);
        if (cta < 36) {
            const unsigned* xw = reinterpret_cast<const unsigned*>(prm.x) + warp * 288;
            float xv[18];
#pragma unroll
            for (int i = 0; i < 9; i++) { unsigned w = __ldg(xw + lane + 32 * i); xv[2 * i] = bf_lo(w); xv[2 * i + 1] = bf_hi(w); }
            if (warp < 2) {
                xh[0] = __bfloat162float(prm.x[(2 * t) * DM + 16 * cta + 8 * warp + g]);
                xh[1] = __bfloat162float(prm.x[(2 * t + 1) * DM + 16 * cta + 8 * warp + g]);
            }
            float mr, rs;
            ln_stats(xv, mr, rs);
            if (lane == 0) { s_stat[2 * warp] = mr; s_stat[2 * warp + 1] = rs; }
        }
#pragma unroll
        for (int i = 0; i < 9; i++) cv[i] = pack_bf2(silu_f(bf_lo(cv[i])), silu_f(bf_hi(cv[i])));
        if (cta < 36) {
#pragma unroll
            for (int i = 0; i < 9; i++) bufArow[32 * i] = cv[i];
        }
    }
    if (tid == 0) {
        *s_epoch = e0;
        atomicAdd(&g_started[e0 & 1], 1u);
    }
    __syncthreads();
    const unsigned epoch = *s_epoch;
    const unsigned tag16 = epoch % 65535u + 1u;
    const unsigned tag2 = epoch % 3u + 1u;
    const unsigned tag32 = epoch + 1u;
    float4* s_red = reinterpret_cast<float4*>(sp + SM_RED);
    const uint32_t bA = bufA + (g * BUFA_PITCH + 2 * t) * 2;
    const int kr = (lane & 7) + 8 * (lane >> 4);
    const int mh = (lane >> 3) & 1;

    auto mod_slice = [&](float4& v) {
        mbar_wait(bar_full + 0, 0);
        TS(18);
        const int tile = warp & 1, kq = warp >> 1;
        float acc[4] = {0.f, 0.f, 0.f, 0.f};
        const uint32_t boxb = sb + mh * 18432;
#pragma unroll
        for (int i = 0; i < 9; i++) {
            const int ks = kq * 9 + i;
            const int r = 16 * ks + kr;
            uint32_t a[4];
            ldsm4t(boxb + r * 32 + ((tile ^ ((r >> 2) & 1)) << 4), a);
            mma16816(acc, a, lds32(bA + ks * 32), lds32(bA + ks * 32 + 16));
        }
        s_red[warp * 32 + lane] = make_float4(acc[0], acc[1], acc[2], acc[3]);
        cons_sync();
        if (warp < 2) {
            v = s_red[warp * 32 + lane];
#pragma unroll
            for (int k = 1; k < 4; k++) { float4 u = s_red[(warp + 2 * k) * 32 + lane]; v.x += u.x; v.y += u.y; v.z += u.z; v.w += u.w; }
        }
    };

    if (cta < 36) {
        TS(17);
        float4 v;
        mod_slice(v);
        if (warp < 2) {
            const int col = 16 * cta + 8 * warp + g;
            const float h0 = ln_mod(xh[0], s_stat[4 * t], s_stat[4 * t + 1], bfr(v.z), bfr(v.x));
            const float h1 = ln_mod(xh[1], s_stat[4 * t + 2], s_stat[4 * t + 3], bfr(v.w), bfr(v.y));
            stg_relaxed1(&g_h[(2 * t) * DM + col], (bf_bits(h0) << 16) | tag16);
            stg_relaxed1(&g_h[(2 * t + 1) * DM + col], (bf_bits(h1) << 16) | tag16);
        }
    }
    TS(1);
    if (cta < NROLE) {
        uint2 hv[9];
        issue_row16(g_h + warp * DM, lane, hv);
        check_row16(g_h + warp * DM, lane, tag16, hv);
        TS(19);
        if (cta < 36) cons_sync();
#pragma unroll
        for (int i = 0; i < 9; i++) bufArow[32 * i] = pack_hi(hv[i].x, hv[i].y);
        cons_sync();
        TS(20);
        mbar_wait(bar_full + 8, 0);
        TS(21);
        const int tile = warp & 1, kq = warp >> 1;
        float acc[4] = {0.f, 0.f, 0.f, 0.f};
        const int ch = 2 * tile + mh;
#pragma unroll
        for (int i = 0; i < 9; i++) {
            const int ks = kq * 9 + i;
            const int r = 16 * ks + kr;
            uint32_t a[4];
            ldsm4t(sb + 36864 + r * 64 + ((ch ^ ((r >> 1) & 3)) << 4), a);
            mma16816(acc, a, lds32(bA + ks * 32), lds32(bA + ks * 32 + 16));
        }
        s_red[warp * 32 + lane] = make_float4(acc[0], acc[1], acc[2], acc[3]);
        cons_sync();
        if (warp < 2) {
            float4 v = s_red[warp * 32 + lane];
#pragma unroll
            for (int k = 1; k < 4; k++) { float4 u = s_red[(warp + 2 * k) * 32 + lane]; v.x += u.x; v.y += u.y; v.z += u.z; v.w += u.w; }
            const int col = 32 * cta + 16 * warp + g;
            stg_relaxed1(&g_q[(2 * t) * 4096 + col], (bf_bits(v.x) << 16) | tag16);
            stg_relaxed1(&g_q[(2 * t + 1) * 4096 + col], (bf_bits(v.y) << 16) | tag16);
            stg_relaxed1(&g_q[(2 * t) * 4096 + col + 8], (bf_bits(v.z) << 16) | tag16);
            stg_relaxed1(&g_q[(2 * t + 1) * 4096 + col + 8], (bf_bits(v.w) << 16) | tag16);
        }
        TS(2);
        if (cta >= 36 && cta < 108) {
#pragma unroll
            for (int i = 0; i < 9; i++) bufArow[32 * i] = cv[i];
            cons_sync();
            float4 v;
            mod_slice(v);
            if (warp < 2) {
                const int colA = 1152 + 32 * (cta - 36) + 8 * warp + g, colB = colA + 16;
                stg_relaxed1(&g_mod[(2 * t) * 3456 + colA], (bf_bits(v.x) << 16) | tag16);
                stg_relaxed1(&g_mod[(2 * t + 1) * 3456 + colA], (bf_bits(v.y) << 16) | tag16);
                stg_relaxed1(&g_mod[(2 * t) * 3456 + colB], (bf_bits(v.z) << 16) | tag16);
                stg_relaxed1(&g_mod[(2 * t + 1) * 3456 + colB], (bf_bits(v.w) << 16) | tag16);
            }
        }
    }
    __syncwarp();
    if (lane == 0) { mbar_arrive(bar_empty + 0); mbar_arrive(bar_empty + 8); }

    int seq = 2;
    {
        uint32_t kpre[2], vpre[2];
        {
            const int key = (lane & 7) + 8 * mh, cs = lane >> 4;
#pragma unroll
            for (int h = 0; h < 2; h++) {
                const int r = 2 * (16 * warp + key) + h;
                kpre[h] = r * 128 + ((cs ^ (r & 7)) << 4);
            }
            const int k8 = (lane & 7), hi = lane >> 4;
            const int vkey = (k8 >> 1) + 8 * (k8 & 1) + 4 * hi;
#pragma unroll
            for (int h = 0; h < 2; h++) {
                const int r = 2 * (16 * warp + vkey) + h;
                vpre[h] = r * 128 + ((mh ^ (r & 7)) << 4);
            }
        }
        uint32_t qf[8][2];
        float o[8][4];
        float m = -INFINITY, l = 0.f;
        int cur = -1, pslot = 0;
        float* scr_o = reinterpret_cast<float*>(sp + SM_SCR);
        float* scr_ml = reinterpret_cast<float*>(sp + SM_ML);
        while (true) {
            const int us = (seq >> 1) % 3;
            const uint32_t cph = (((seq >> 1) - 1) / 3) & 1;
            mbar_wait(bar_ctrl + 8 * us, cph);
            const int np = meta[us].x, nslot = meta[us].y;
            if (np != cur) {
                if (cur >= 0) {
#pragma unroll
                    for (int of = 4; of <= 16; of <<= 1) l += __shfl_xor_sync(0xffffffffu, l, of);
                    if (t == 0) {
#pragma unroll
                        for (int mt = 0; mt < 8; mt++) {
                            scr_o[(warp * 2 + 0) * 128 + 16 * mt + g] = o[mt][0];
                            scr_o[(warp * 2 + 1) * 128 + 16 * mt + g] = o[mt][1];
                            scr_o[(warp * 2 + 0) * 128 + 16 * mt + g + 8] = o[mt][2];
                            scr_o[(warp * 2 + 1) * 128 + 16 * mt + g + 8] = o[mt][3];
                        }
                    }
                    if (lane < 2) { scr_ml[(warp * 2 + lane) * 2] = m; scr_ml[(warp * 2 + lane) * 2 + 1] = l; }
                    cons_sync();
                    {
                        const int h = tid >> 7, d = tid & 127;
                        float M = -INFINITY;
#pragma unroll
                        for (int w = 0; w < 8; w++) M = fmaxf(M, scr_ml[(w * 2 + h) * 2]);
                        float O = 0.f, L = 0.f;
#pragma unroll
                        for (int w = 0; w < 8; w++) {
                            const float f = ex2((scr_ml[(w * 2 + h) * 2] - M) * LOG2E);
                            O += f * scr_o[(w * 2 + h) * 128 + d];
                            L += f * scr_ml[(w * 2 + h) * 2 + 1];
                        }
                        unsigned long long* rec = g_part + ((size_t)cur * MAXS + pslot) * PSTRIDE;
                        stg_relaxed64(rec + tid, __float_as_uint(O), tag32);
                        if (d == 0) {
                            stg_relaxed64(rec + 256 + 2 * h, __float_as_uint(M), tag32);
                            stg_relaxed64(rec + 257 + 2 * h, __float_as_uint(L), tag32);
                        }
                    }
                    cons_sync();
                }
                if (np < 0) break;
                cur = np; pslot = nslot;
                m = -INFINITY; l = 0.f;
#pragma unroll
                for (int mt = 0; mt < 8; mt++) { o[mt][0] = o[mt][1] = o[mt][2] = o[mt][3] = 0.f; }
                const unsigned* qb = g_q + (cur >> 4) * 4096 + (cur & 15) * 256 + (g & 1) * 128 + 2 * t;
                unsigned spins = 0;
                while (true) {
                    bool ok = true;
#pragma unroll
                    for (int ks = 0; ks < 8; ks++) {
                        uint2 a = ldg_relaxed2(qb + 16 * ks), b = ldg_relaxed2(qb + 16 * ks + 8);
                        ok = ok && ((a.x & 0xffffu) == tag16) && ((a.y & 0xffffu) == tag16) &&
                             ((b.x & 0xffffu) == tag16) && ((b.y & 0xffffu) == tag16);
                        qf[ks][0] = pack_hi(a.x, a.y);
                        qf[ks][1] = pack_hi(b.x, b.y);
                    }
                    if (__all_sync(0xffffffffu, ok)) break;
                    if (++spins > SPIN_LIMIT) TRAP_AT(__LINE__);
                }
            }
            if (seq == 2) TS(3);
            if (seq == 6) TS(4);
            const int sK = seq % NSLOT;
            const uint32_t ph = (seq / NSLOT) & 1;
            const uint32_t kb = sb + SM_RING + sK * SLOT, vb = kb + SLOT;
            mbar_wait(bar_full + 8 * sK, ph);
            float c0[4] = {0.f, 0.f, 0.f, 0.f}, c1[4] = {0.f, 0.f, 0.f, 0.f};
#pragma unroll
            for (int ks = 0; ks < 8; ks += 2) {
                uint32_t a[4], b[4];
                ldsm4(kb + (kpre[ks >> 2] ^ ((ks & 3) << 5)), a);
                ldsm4(kb + (kpre[(ks + 1) >> 2] ^ (((ks + 1) & 3) << 5)), b);
                mma16816(c0, a, qf[ks][0], qf[ks][1]);
                mma16816(c1, b, qf[ks + 1][0], qf[ks + 1][1]);
            }
            __syncwarp();
            if (lane == 0) mbar_arrive(bar_empty + 8 * sK);
            float s0 = (t & 1) ? (c0[1] + c1[1]) : (c0[0] + c1[0]);
            float s1 = (t & 1) ? (c0[3] + c1[3]) : (c0[2] + c1[2]);
            s0 = bfr(bfr(s0) * QSCALE);
            s1 = bfr(bfr(s1) * QSCALE);
            float bm = fmaxf(s0, s1);
            if (__any_sync(0xffffffffu, bm > m)) {
#pragma unroll
                for (int of = 4; of <= 16; of <<= 1) bm = fmaxf(bm, __shfl_xor_sync(0xffffffffu, bm, of));
                const float mn = fmaxf(m, bm);
                const float al = ex2((m - mn) * LOG2E);
                m = mn; l *= al;
                const float alo = __shfl_xor_sync(0xffffffffu, al, 1);
                const float a0 = (t & 1) ? alo : al, a1 = (t & 1) ? al : alo;
#pragma unroll
                for (int mt = 0; mt < 8; mt++) { o[mt][0] *= a0; o[mt][1] *= a1; o[mt][2] *= a0; o[mt][3] *= a1; }
            }
            const float p0 = ex2((s0 - m) * LOG2E), p1 = ex2((s1 - m) * LOG2E);
            l += p0 + p1;
            const unsigned pk = pack_bf2(p0, p1);
            const unsigned pb0 = __shfl_sync(0xffffffffu, pk, 4 * t + (g & 1));
            const unsigned pb1 = __shfl_sync(0xffffffffu, pk, 4 * (t + 4) + (g & 1));
            mbar_wait(bar_full + 8 * (sK + 1), ph);
#pragma unroll
            for (int mt = 0; mt < 8; mt++) {
                uint32_t a[4];
                ldsm4t(vb + (vpre[mt >> 2] ^ ((mt & 3) << 5)), a);
                mma16816(o[mt], a, pb0, pb1);
            }
            __syncwarp();
            if (lane == 0) mbar_arrive(bar_empty + 8 * (sK + 1));
            seq += 2;
        }
    }
    TS(5);
    if (tid == 0) TSV(16, seq);
    if (cta >= NROLE) return;
    if (tid == 0) mbar_arrive(bar_sig);

    const int hkv = cta >> 3, ns = cta & 7;
    uint2 cbv[9], sbv[9];
    const unsigned* cbp = g_mod + warp * 3456 + 4 * DM;
    const unsigned* sbp = g_mod + warp * 3456 + 3 * DM;
    issue_row16(cbp, lane, cbv);
    issue_row16(sbp, lane, sbv);
    const int src = lane & 15, ch3 = 2 * warp + (lane >> 4);
    const int v0 = ns * 576 + 36 * hkv + 4 * ch3;
    const bool t3act = (warp < 4 || (warp == 4 && lane < 16));
    const int col3 = (v0 + (src & 3)) >> 3, b3 = (v0 + (src & 3)) & 7;
    float x3 = 0.f; unsigned gaw = 0;
    if (t3act && src < 4) {
        x3 = __bfloat162float(prm.x[b3 * DM + col3]);
        gaw = ldg_relaxed1(&g_mod[b3 * 3456 + 2 * DM + col3]);
    }
    unsigned gbw = 0;
    const int col5 = 8 * cta + (tid >> 3), b5 = tid & 7;
    if (cta < 72 && tid < 64) gbw = ldg_relaxed1(&g_mod[b5 * 3456 + 5 * DM + col5]);
    {
        const int p = warp * HKV + hkv;
        const unsigned nj = (unsigned)sp[SM_NJ + p] + 1u;
        const unsigned long long* rec = g_part + (size_t)p * MAXS * PSTRIDE;
        float M0 = -INFINITY, M1 = -INFINITY, L0 = 0.f, L1 = 0.f;
        float O[8];
#pragma unroll
        for (int i = 0; i < 8; i++) O[i] = 0.f;
        for (unsigned s = 0; s < nj; s += 2) {
            const bool two = s + 1 < nj;
            const unsigned long long* r0 = rec + (size_t)s * PSTRIDE;
            const unsigned long long* r1 = two ? r0 + PSTRIDE : r0;
            ulonglong2 a[6], b[6];
            unsigned spins = 0;
            while (true) {
#pragma unroll
                for (int j = 0; j < 4; j++) a[j] = ldg_relaxed2x64(r0 + 2 * (32 * j + lane));
                a[4] = ldg_relaxed2x64(r0 + 256); a[5] = ldg_relaxed2x64(r0 + 258);
#pragma unroll
                for (int j = 0; j < 4; j++) b[j] = ldg_relaxed2x64(r1 + 2 * (32 * j + lane));
                b[4] = ldg_relaxed2x64(r1 + 256); b[5] = ldg_relaxed2x64(r1 + 258);
                bool ok = true;
#pragma unroll
                for (int j = 0; j < 6; j++)
                    ok = ok && (unsigned)(a[j].x >> 32) == tag32 && (unsigned)(a[j].y >> 32) == tag32 &&
                         (unsigned)(b[j].x >> 32) == tag32 && (unsigned)(b[j].y >> 32) == tag32;
                if (ok) break;
                if (++spins > SPIN_LIMIT) TRAP_AT(__LINE__);
            }
#pragma unroll
            for (int q = 0; q < 2; q++) {
                if (q == 1 && !two) break;
                const ulonglong2* r = q ? b : a;
                const float m0 = __uint_as_float((unsigned)r[4].x), l0 = __uint_as_float((unsigned)r[4].y);
                const float m1 = __uint_as_float((unsigned)r[5].x), l1 = __uint_as_float((unsigned)r[5].y);
                const float N0 = fmaxf(M0, m0), N1 = fmaxf(M1, m1);
                const float fo0 = ex2((M0 - N0) * LOG2E), fn0 = ex2((m0 - N0) * LOG2E);
                const float fo1 = ex2((M1 - N1) * LOG2E), fn1 = ex2((m1 - N1) * LOG2E);
                M0 = N0; M1 = N1;
                L0 = L0 * fo0 + l0 * fn0; L1 = L1 * fo1 + l1 * fn1;
#pragma unroll
                for (int j = 0; j < 4; j++) {
                    const float fo = j < 2 ? fo0 : fo1, fn = j < 2 ? fn0 : fn1;
                    O[2 * j] = O[2 * j] * fo + __uint_as_float((unsigned)r[j].x) * fn;
                    O[2 * j + 1] = O[2 * j + 1] * fo + __uint_as_float((unsigned)r[j].y) * fn;
                }
            }
        }
        const float i0 = __frcp_rn(L0), i1 = __frcp_rn(L1);
        unsigned* ob = reinterpret_cast<unsigned*>(sp + SM_SCR + warp * BUFO_PITCH * 2) + lane;
#pragma unroll
        for (int j = 0; j < 4; j++) {
            const float iv = j < 2 ? i0 : i1;
            ob[32 * j] = pack_bf2(O[2 * j] * iv, O[2 * j + 1] * iv);
        }
    }
    cons_sync();
    TS(6);
    if (warp < 5) {
        const int s0 = seq % NSLOT, s1 = (seq + 1) % NSLOT;
        mbar_wait(bar_full + 8 * s0, (seq / NSLOT) & 1);
        const uint32_t w0 = sb + SM_RING + s0 * SLOT, w1 = sb + SM_RING + s1 * SLOT;
        const uint32_t bO = sb + SM_SCR + (g * BUFO_PITCH + 2 * t) * 2;
        int cb = 16 * warp + 8 * mh;
        if (cb > 64) cb = 64;
        float acc[2][4] = {{0.f, 0.f, 0.f, 0.f}, {0.f, 0.f, 0.f, 0.f}};
#pragma unroll
        for (int ks = 0; ks < 16; ks++) {
            if (ks == 12) mbar_wait(bar_full + 8 * s1, ((seq + 1) / NSLOT) & 1);
            const int r = 16 * ks + kr;
            const uint32_t addr = (ks < 12 ? w0 + r * 144 : w1 + (r - 192) * 144) + cb * 2;
            uint32_t a[4];
            ldsm4t(addr, a);
            mma16816(acc[ks & 1], a, lds32(bO + ks * 32), lds32(bO + ks * 32 + 16));
        }
        unsigned* dst = g_wop + (size_t)hkv * (DM * NB) + (72 * ns + 16 * warp + g) * 8 + 2 * t;
        stg_relaxed2(dst, (__float_as_uint(acc[0][0] + acc[1][0]) & ~3u) | tag2, (__float_as_uint(acc[0][1] + acc[1][1]) & ~3u) | tag2);
        if (warp < 4)
            stg_relaxed2(dst + 64, (__float_as_uint(acc[0][2] + acc[1][2]) & ~3u) | tag2, (__float_as_uint(acc[0][3] + acc[1][3]) & ~3u) | tag2);
    }
    TS(7);
    if (t3act) {
        const unsigned amask = warp < 4 ? 0xffffffffu : 0x0000ffffu;
        const unsigned* ptr = g_wop + (size_t)src * (DM * NB) + v0;
        uint4 v;
        unsigned spins = 0;
        while (true) {
            v = ldg_relaxed4(ptr);
            if ((v.x & 3u) == tag2 && (v.y & 3u) == tag2 && (v.z & 3u) == tag2 && (v.w & 3u) == tag2) break;
            if (++spins > SPIN_LIMIT) TRAP_AT(__LINE__);
        }
        float f0 = __uint_as_float(v.x & ~3u), f1 = __uint_as_float(v.y & ~3u), f2 = __uint_as_float(v.z & ~3u), f3 = __uint_as_float(v.w & ~3u);
#pragma unroll
        for (int of = 1; of <= 8; of <<= 1) {
            f0 += __shfl_xor_sync(amask, f0, of); f1 += __shfl_xor_sync(amask, f1, of);
            f2 += __shfl_xor_sync(amask, f2, of); f3 += __shfl_xor_sync(amask, f3, of);
        }
        if (src < 4) {
            spins = 0;
            while ((gaw & 0xffffu) != tag16) {
                gaw = ldg_relaxed1(&g_mod[b3 * 3456 + 2 * DM + col3]);
                if (++spins > SPIN_LIMIT) TRAP_AT(__LINE__);
            }
            const float a = bfr(src == 0 ? f0 : src == 1 ? f1 : src == 2 ? f2 : f3);
            const float x2 = x3 + bfr(bf_hi(gaw) * a);
            stg_relaxed1(&g_x2[b3 * DM + col3], (bf_bits(x2) << 16) | tag16);
        }
    }
    TS(8);
    {
        uint2 xv2[9];
        issue_row16(g_x2 + warp * DM, lane, xv2);
        check_row16(cbp, lane, tag16, cbv);
        check_row16(sbp, lane, tag16, sbv);
        check_row16(g_x2 + warp * DM, lane, tag16, xv2);
        float xf[18];
#pragma unroll
        for (int i = 0; i < 9; i++) { xf[2 * i] = bf_hi(xv2[i].x); xf[2 * i + 1] = bf_hi(xv2[i].y); }
        float mr, rs;
        ln_stats(xf, mr, rs);
#pragma unroll
        for (int i = 0; i < 9; i++) {
            const float h0 = ln_mod(xf[2 * i], mr, rs, bf_hi(cbv[i].x), bf_hi(sbv[i].x));
            const float h1 = ln_mod(xf[2 * i + 1], mr, rs, bf_hi(cbv[i].y), bf_hi(sbv[i].y));
            bufArow[32 * i] = pack_bf2(h0, h1);
        }
        if (tid < 48) *reinterpret_cast<unsigned*>(sp + SM_ACT + ((tid / 6) * ACT_PITCH + 36 + 2 * (tid % 6)) * 2) = 0;
    }
    cons_sync();
    TS(9);
    unsigned x2w = 0;
    if (cta < 72 && tid < 64) x2w = ldg_relaxed1(&g_x2[b5 * DM + col5]);
    if (warp < 5) {
        uint32_t sl[4];
#pragma unroll
        for (int i = 0; i < 4; i++) {
            const int sq = seq + 1 + i;
            mbar_wait(bar_full + 8 * (sq % NSLOT), (sq / NSLOT) & 1);
            sl[i] = sb + SM_RING + (sq % NSLOT) * SLOT;
        }
        uint32_t base[3];
        base[0] = mh ? sl[1] : sl[0] + 9216;
        base[1] = mh ? sl[2] : sl[1] + 15360;
        base[2] = mh ? sl[3] : sl[2] + 15360;
        float acc[4][4];
#pragma unroll
        for (int i = 0; i < 4; i++) acc[i][0] = acc[i][1] = acc[i][2] = acc[i][3] = 0.f;
#pragma unroll
        for (int ks = 0; ks < 36; ks++) {
            const int r = (16 * ks) % 192 + kr;
            uint32_t a[4];
            ldsm4t(base[ks / 12] + r * 80 + warp * 16, a);
            mma16816(acc[ks & 3], a, lds32(bA + ks * 32), lds32(bA + ks * 32 + 16));
        }
        const int cl = 8 * warp + g - 4 * (cta & 1);
#pragma unroll
        for (int e = 0; e < 2; e++) {
            const float gt = bfr(acc[0][e] + acc[1][e] + acc[2][e] + acc[3][e]);
            const float up = bfr(acc[0][2 + e] + acc[1][2 + e] + acc[2][2 + e] + acc[3][2 + e]);
            const float u2 = 1.5957691216057308f * (gt + 0.044715f * gt * gt * gt);
            const float ge = bfr(__fdividef(gt, 1.0f + __expf(-u2)));
            if (cl >= 0 && cl < 36)
                *reinterpret_cast<__nv_bfloat16*>(sp + SM_ACT + ((2 * t + e) * ACT_PITCH + cl) * 2) = __float2bfloat16_rn(ge * up);
        }
    }
    cons_sync();
    TS(10);
    {
        const int s4 = (seq + 4) % NSLOT, s5 = (seq + 5) % NSLOT;
        mbar_wait(bar_full + 8 * s4, ((seq + 4) / NSLOT) & 1);
        mbar_wait(bar_full + 8 * s5, ((seq + 5) / NSLOT) & 1);
        const uint32_t d4 = sb + SM_RING + s4 * SLOT + 15360, d5 = sb + SM_RING + s5 * SLOT;
        const uint32_t bAct = sb + SM_ACT + (g * ACT_PITCH + 2 * t) * 2;
        uint32_t bf[3][2];
#pragma unroll
        for (int ks = 0; ks < 3; ks++) { bf[ks][0] = lds32(bAct + ks * 32); bf[ks][1] = lds32(bAct + ks * 32 + 16); }
        for (int tile = warp; tile < 36; tile += 8) {
            const int cbk = tile >> 2;
            const uint32_t box = cbk < 3 ? d4 + cbk * 5120 : d5 + (cbk - 3) * 5120;
            const int ch = (tile & 3) * 2 + mh;
            float acc[4] = {0.f, 0.f, 0.f, 0.f};
#pragma unroll
            for (int ks = 0; ks < 3; ks++) {
                int r = 16 * ks + kr;
                if (r > 35) r = 35;
                uint32_t a[4];
                ldsm4t(box + r * 128 + ((ch ^ (r & 7)) << 4), a);
                mma16816(acc, a, bf[ks][0], bf[ks][1]);
            }
            unsigned* dst = g_dnp + (size_t)cta * (DM * NB) + (16 * tile + g) * 8 + 2 * t;
            stg_relaxed2(dst, (__float_as_uint(acc[0]) & ~3u) | tag2, (__float_as_uint(acc[1]) & ~3u) | tag2);
            stg_relaxed2(dst + 64, (__float_as_uint(acc[2]) & ~3u) | tag2, (__float_as_uint(acc[3]) & ~3u) | tag2);
        }
    }
    TS(11);
    if (cta < 72) {
        const int ch = lane & 15, sl = lane >> 4;
        const unsigned* ptr = g_dnp + (size_t)(16 * warp + sl) * (DM * NB) + 64 * cta + 4 * ch;
        uint4 v[8];
#pragma unroll
        for (int i = 0; i < 8; i++) v[i] = ldg_relaxed4(ptr + (size_t)(2 * i) * (DM * NB));
        unsigned spins = 0;
        while (true) {
            bool ok = true;
#pragma unroll
            for (int i = 0; i < 8; i++) {
                if ((v[i].x & 3u) != tag2 || (v[i].y & 3u) != tag2 || (v[i].z & 3u) != tag2 || (v[i].w & 3u) != tag2) {
                    v[i] = ldg_relaxed4(ptr + (size_t)(2 * i) * (DM * NB));
                    ok = false;
                }
            }
            if (ok) break;
            if (++spins > SPIN_LIMIT) TRAP_AT(__LINE__);
        }
        float f[4] = {0.f, 0.f, 0.f, 0.f};
#pragma unroll
        for (int i = 0; i < 8; i++) {
            f[0] += __uint_as_float(v[i].x & ~3u); f[1] += __uint_as_float(v[i].y & ~3u);
            f[2] += __uint_as_float(v[i].z & ~3u); f[3] += __uint_as_float(v[i].w & ~3u);
        }
#pragma unroll
        for (int e = 0; e < 4; e++) f[e] += __shfl_xor_sync(0xffffffffu, f[e], 16);
        if (lane < 16) s_red[warp * 16 + ch] = make_float4(f[0], f[1], f[2], f[3]);
        cons_sync();
        if (tid < 64) {
            spins = 0;
            while ((gbw & 0xffffu) != tag16) {
                gbw = ldg_relaxed1(&g_mod[b5 * 3456 + 5 * DM + col5]);
                if (++spins > SPIN_LIMIT) TRAP_AT(__LINE__);
            }
            const float* r = reinterpret_cast<const float*>(s_red);
            float s = 0.f;
#pragma unroll
            for (int w = 0; w < 8; w++) s += r[w * 64 + tid];
            const float o = bf_hi(x2w) + bfr(bf_hi(gbw) * bfr(s));
            prm.out[b5 * DM + col5] = __float2bfloat16_rn(o);
        }
        TS(12);
    }
}

typedef CUresult (*EncodeFn)(CUtensorMap*, CUtensorMapDataType, cuuint32_t, void*, const cuuint64_t*, const cuuint64_t*,
                             const cuuint32_t*, const cuuint32_t*, CUtensorMapInterleave, CUtensorMapSwizzle,
                             CUtensorMapL2promotion, CUtensorMapFloatOOBfill);

bool make_map(EncodeFn fn, CUtensorMap* m, const void* ptr, uint64_t inner, uint64_t outer, uint64_t stride_bytes,
              uint32_t box_inner, uint32_t box_outer, CUtensorMapSwizzle sw, CUtensorMapL2promotion promo) {
    cuuint64_t dims[2] = {inner, outer};
    cuuint64_t strides[1] = {stride_bytes};
    cuuint32_t box[2] = {box_inner, box_outer};
    cuuint32_t es[2] = {1, 1};
    return fn(m, CU_TENSOR_MAP_DATA_TYPE_BFLOAT16, 2, const_cast<void*>(ptr), dims, strides, box, es,
              CU_TENSOR_MAP_INTERLEAVE_NONE, sw, promo, CU_TENSOR_MAP_FLOAT_OOB_FILL_NONE) == CUDA_SUCCESS;
}

}

extern "C" void kernel_launch(void* const* d_in, const int* in_sizes, int n_in, void* d_out, int out_size) {
    (void)in_sizes; (void)n_in; (void)out_size;
    static EncodeFn encode = nullptr;
    static int num_sms = 0;
    if (!encode) {
        void* fn = nullptr;
        cudaDriverEntryPointQueryResult qres;
        cudaGetDriverEntryPoint("cuTensorMapEncodeTiled", &fn, cudaEnableDefault, &qres);
        encode = (EncodeFn)fn;
        int dev = 0;
        cudaGetDevice(&dev);
        cudaDeviceGetAttribute(&num_sms, cudaDevAttrMultiProcessorCount, dev);
        cudaFuncSetAttribute(fused_kernel, cudaFuncAttributeMaxDynamicSharedMemorySize, SMEM_BYTES);
    }
    CUtensorMap tmK, tmV, tmMod, tmQ, tmO, tmG, tmU, tmD;
    const uint64_t kvrows = (uint64_t)NB * HKV * SK * 2;
    make_map(encode, &tmK, d_in[1], 64, kvrows, 128, 64, 256, CU_TENSOR_MAP_SWIZZLE_128B, CU_TENSOR_MAP_L2_PROMOTION_L2_256B);
    make_map(encode, &tmV, d_in[2], 64, kvrows, 128, 64, 256, CU_TENSOR_MAP_SWIZZLE_128B, CU_TENSOR_MAP_L2_PROMOTION_L2_256B);
    make_map(encode, &tmQ, d_in[3], 4096, DM, 8192, 32, 192, CU_TENSOR_MAP_SWIZZLE_64B, CU_TENSOR_MAP_L2_PROMOTION_L2_128B);
    make_map(encode, &tmO, d_in[4], DM, 4096, DM * 2, 72, 64, CU_TENSOR_MAP_SWIZZLE_NONE, CU_TENSOR_MAP_L2_PROMOTION_L2_128B);
    make_map(encode, &tmG, d_in[6], FF, DM, FF * 2, 40, 192, CU_TENSOR_MAP_SWIZZLE_NONE, CU_TENSOR_MAP_L2_PROMOTION_L2_128B);
    make_map(encode, &tmU, d_in[7], FF, DM, FF * 2, 40, 192, CU_TENSOR_MAP_SWIZZLE_NONE, CU_TENSOR_MAP_L2_PROMOTION_L2_128B);
    make_map(encode, &tmD, d_in[8], DM, FF, DM * 2, 64, 36, CU_TENSOR_MAP_SWIZZLE_128B, CU_TENSOR_MAP_L2_PROMOTION_L2_128B);
    make_map(encode, &tmMod, d_in[10], 6 * DM, DM, 6 * DM * 2, 16, 192, CU_TENSOR_MAP_SWIZZLE_32B, CU_TENSOR_MAP_L2_PROMOTION_L2_128B);
    Params prm;
    prm.x = (const __nv_bfloat16*)d_in[0];
    prm.c = (const __nv_bfloat16*)d_in[9];
    prm.wt[0] = (const unsigned char*)d_in[4];
    prm.wt[1] = (const unsigned char*)d_in[6];
    prm.wt[2] = (const unsigned char*)d_in[7];
    prm.wt[3] = (const unsigned char*)d_in[8];
    prm.out = (__nv_bfloat16*)d_out;
    int grid = num_sms < MAXCTA ? num_sms : MAXCTA;
    fused_kernel<<<grid, NTHREADS, SMEM_BYTES>>>(tmK, tmV, tmMod, tmQ, tmO, tmG, tmU, tmD, prm);
}
```

```cpp
#include <cuda_runtime.h>
#include <cuda_bf16.h>
#include <cuda.h>
#include <stdint.h>

namespace {

constexpr int NB = 8;
constexpr int DM = 576;
constexpr int HKV = 16;
constexpr int SK = 8192;
constexpr int DH = 128;
constexpr int FF = 4608;
constexpr int NPAIR = NB * HKV;
constexpr int UKEYS = 128;
constexpr int UNITS = SK / UKEYS;
constexpr int SLOT = 32768;
constexpr int NSLOT = 6;
constexpr int NROLE = 128;
constexpr int MAXCTA = 132;
constexpr int MAXS = MAXCTA + 1;
constexpr int PSTRIDE = 264;
constexpr int NCONS = 256;
constexpr int NTHREADS = 288;

constexpr int SM_SCR = 0;
constexpr int SM_RING = 8192;
constexpr int SM_BUFA = SM_RING + NSLOT * SLOT;
constexpr int BUFA_PITCH = 584;
constexpr int SM_RED = SM_BUFA + 8 * BUFA_PITCH * 2;
constexpr int SM_ACT = SM_RED + 4096;
constexpr int ACT_PITCH = 56;
constexpr int SM_ML = SM_ACT + 8 * ACT_PITCH * 2;
constexpr int SM_STAT = SM_ML + 128;
constexpr int SM_META = SM_STAT + 64;
constexpr int SM_BAR = SM_META + 32;
constexpr int SM_EPOCH = SM_BAR + 16 * 8;
constexpr int SM_NJ = SM_EPOCH + 16;
constexpr int SM_TOTAL = SM_NJ + 128;
constexpr int SMEM_BYTES = SM_TOTAL + 1024;
constexpr int BUFO_PITCH = 264;

__device__ __align__(16) unsigned g_ctr[2][NPAIR];
__device__ unsigned g_epoch;
__device__ unsigned g_started[2];
__device__ __align__(16) unsigned g_h[NB * DM];
__device__ __align__(16) unsigned g_mod[NB * 6 * DM];
__device__ __align__(16) unsigned g_q[NB * 4096];
__device__ __align__(16) unsigned long long g_part[(size_t)NPAIR * MAXS * PSTRIDE];
__device__ __align__(16) unsigned g_wop[HKV * DM * NB];
__device__ __align__(16) unsigned g_x2[NB * DM];
__device__ __align__(16) unsigned g_dnp[(size_t)NROLE * DM * NB];

struct Params {
    const __nv_bfloat16* x;
    const __nv_bfloat16* c;
    const unsigned char* wt[4];
    __nv_bfloat16* out;
};

#define TRAP_AT(line) __trap()
#define TS(i)
#define TSV(i, v)

__device__ __forceinline__ uint32_t smem_u32(const void* p) { return (uint32_t)__cvta_generic_to_shared(p); }
__device__ __forceinline__ void mbar_init(uint32_t bar, uint32_t cnt) {
    asm volatile("mbarrier.init.shared::cta.b64 [%0], %1;" ::"r"(bar), "r"(cnt) : "memory");
}
__device__ __forceinline__ void mbar_expect_tx(uint32_t bar, uint32_t bytes) {
    asm volatile("mbarrier.arrive.expect_tx.shared::cta.b64 _, [%0], %1;" ::"r"(bar), "r"(bytes) : "memory");
}
__device__ __forceinline__ void mbar_arrive(uint32_t bar) {
    asm volatile("mbarrier.arrive.shared::cta.b64 _, [%0];" ::"r"(bar) : "memory");
}
__device__ __forceinline__ bool mbar_try(uint32_t bar, uint32_t parity) {
    uint32_t ok;
    asm volatile(
        "{\n.reg .pred p;\n"
        "mbarrier.try_wait.parity.shared::cta.b64 p, [%1], %2;\n"
        "selp.u32 %0, 1, 0, p;\n}\n"
        : "=r"(ok) : "r"(bar), "r"(parity) : "memory");
    return ok != 0;
}
__device__ __noinline__ void mbar_wait_slow(uint32_t bar, uint32_t parity) {
    unsigned long long t0, t1;
    asm volatile("mov.u64 %0, %globaltimer;" : "=l"(t0));
    while (!mbar_try(bar, parity)) {
        asm volatile("mov.u64 %0, %globaltimer;" : "=l"(t1));
        if (t1 - t0 > 4000000000ull) TRAP_AT(__LINE__);
    }
}
__device__ __forceinline__ void mbar_wait(uint32_t bar, uint32_t parity) {
    if (!mbar_try(bar, parity)) mbar_wait_slow(bar, parity);
}
__device__ __forceinline__ void tma2d(uint32_t dst, const CUtensorMap* map, int c0, int c1, uint32_t bar) {
    asm volatile(
        "cp.async.bulk.tensor.2d.shared::cluster.global.mbarrier::complete_tx::bytes [%0], [%1, {%3, %4}], [%2];"
        ::"r"(dst), "l"((uint64_t)map), "r"(bar), "r"(c0), "r"(c1) : "memory");
}
__device__ __forceinline__ void tma2d_hint(uint32_t dst, const CUtensorMap* map, int c0, int c1, uint32_t bar, uint64_t pol) {
    asm volatile(
        "cp.async.bulk.tensor.2d.shared::cluster.global.mbarrier::complete_tx::bytes.L2::cache_hint [%0], [%1, {%3, %4}], [%2], %5;"
        ::"r"(dst), "l"((uint64_t)map), "r"(bar), "r"(c0), "r"(c1), "l"(pol) : "memory");
}
__device__ __forceinline__ void l2_prefetch(const void* p, uint32_t bytes) {
    asm volatile("cp.async.bulk.prefetch.L2.global [%0], %1;" ::"l"(p), "r"(bytes) : "memory");
}
__device__ __forceinline__ void ldsm4(uint32_t addr, uint32_t (&r)[4]) {
    asm volatile("ldmatrix.sync.aligned.m8n8.x4.shared.b16 {%0,%1,%2,%3}, [%4];"
                 : "=r"(r[0]), "=r"(r[1]), "=r"(r[2]), "=r"(r[3]) : "r"(addr) : "memory");
}
__device__ __forceinline__ void ldsm4t(uint32_t addr, uint32_t (&r)[4]) {
    asm volatile("ldmatrix.sync.aligned.m8n8.x4.trans.shared.b16 {%0,%1,%2,%3}, [%4];"
                 : "=r"(r[0]), "=r"(r[1]), "=r"(r[2]), "=r"(r[3]) : "r"(addr) : "memory");
}
__device__ __forceinline__ void mma16816(float (&c)[4], const uint32_t (&a)[4], uint32_t b0, uint32_t b1) {
    asm volatile(
        "mma.sync.aligned.m16n8k16.row.col.f32.bf16.bf16.f32 {%0,%1,%2,%3}, {%4,%5,%6,%7}, {%8,%9}, {%0,%1,%2,%3};"
        : "+f"(c[0]), "+f"(c[1]), "+f"(c[2]), "+f"(c[3])
        : "r"(a[0]), "r"(a[1]), "r"(a[2]), "r"(a[3]), "r"(b0), "r"(b1));
}
__device__ __forceinline__ void cons_sync() { asm volatile("bar.sync 1, 256;" ::: "memory"); }
__device__ __forceinline__ uint32_t lds32(uint32_t addr) {
    uint32_t v; asm volatile("ld.shared.u32 %0, [%1];" : "=r"(v) : "r"(addr) : "memory"); return v;
}
__device__ __forceinline__ uint2 ldg_relaxed2(const unsigned* p) {
    uint2 v; asm volatile("ld.relaxed.gpu.global.v2.u32 {%0,%1}, [%2];" : "=r"(v.x), "=r"(v.y) : "l"(p) : "memory"); return v;
}
__device__ __forceinline__ uint4 ldg_relaxed4(const unsigned* p) {
    uint4 v; asm volatile("ld.relaxed.gpu.global.v4.u32 {%0,%1,%2,%3}, [%4];"
                          : "=r"(v.x), "=r"(v.y), "=r"(v.z), "=r"(v.w) : "l"(p) : "memory"); return v;
}
__device__ __forceinline__ unsigned ldg_relaxed1(const unsigned* p) {
    unsigned v; asm volatile("ld.relaxed.gpu.global.u32 %0, [%1];" : "=r"(v) : "l"(p) : "memory"); return v;
}
__device__ __forceinline__ void stg_relaxed1(unsigned* p, unsigned v) {
    asm volatile("st.relaxed.gpu.global.u32 [%0], %1;" ::"l"(p), "r"(v) : "memory");
}
__device__ __forceinline__ void stg_relaxed2(unsigned* p, unsigned a, unsigned b) {
    asm volatile("st.relaxed.gpu.global.v2.u32 [%0], {%1,%2};" ::"l"(p), "r"(a), "r"(b) : "memory");
}
__device__ __forceinline__ ulonglong2 ldg_relaxed2x64(const unsigned long long* p) {
    ulonglong2 v; asm volatile("ld.relaxed.gpu.global.v2.b64 {%0,%1}, [%2];" : "=l"(v.x), "=l"(v.y) : "l"(p) : "memory"); return v;
}
__device__ __forceinline__ void stg_relaxed64(unsigned long long* p, unsigned lo, unsigned hi) {
    asm volatile("{\n.reg .b64 v;\nmov.b64 v, {%1,%2};\nst.relaxed.gpu.global.b64 [%0], v;\n}\n" ::"l"(p), "r"(lo), "r"(hi) : "memory");
}
__device__ __forceinline__ float ex2(float x) { float y; asm("ex2.approx.ftz.f32 %0, %1;" : "=f"(y) : "f"(x)); return y; }

__device__ __forceinline__ float bfr(float x) { return __bfloat162float(__float2bfloat16_rn(x)); }
__device__ __forceinline__ unsigned bf_bits(float x) { return (unsigned)__bfloat16_as_ushort(__float2bfloat16_rn(x)); }
__device__ __forceinline__ float bf_hi(unsigned w) { return __uint_as_float(w & 0xffff0000u); }
__device__ __forceinline__ float bf_lo(unsigned w) { return __uint_as_float(w << 16); }
__device__ __forceinline__ unsigned pack_hi(unsigned lo_word, unsigned hi_word) {
    return __byte_perm(lo_word, hi_word, 0x7632);
}
__device__ __forceinline__ unsigned pack_bf2(float lo, float hi) {
    unsigned r; asm("cvt.rn.bf16x2.f32 %0, %1, %2;" : "=r"(r) : "f"(hi), "f"(lo)); return r;
}
constexpr float LOG2E = 1.4426950408889634f;
constexpr float QSCALE = 0.08838834764831845f;
constexpr unsigned SPIN_LIMIT = 1u << 24;

#define KV_START 1
#define TAILW_MODE 1
#define KV_EF 1
#define WPF_AT 40
#define PF_MIN 6

__device__ __forceinline__ void issue_row16(const unsigned* base, int lane, uint2 (&v)[9]) {
#pragma unroll
    for (int i = 0; i < 9; i++) v[i] = ldg_relaxed2(base + 2 * (lane + 32 * i));
}
__device__ __forceinline__ void check_row16(const unsigned* base, int lane, unsigned tag16, uint2 (&v)[9]) {
    unsigned spins = 0;
    while (true) {
        bool ok = true;
#pragma unroll
        for (int i = 0; i < 9; i++) {
            if ((v[i].x & 0xffffu) != tag16 || (v[i].y & 0xffffu) != tag16) {
                v[i] = ldg_relaxed2(base + 2 * (lane + 32 * i));
                ok = false;
            }
        }
        if (ok) break;
        if (++spins > SPIN_LIMIT) TRAP_AT(__LINE__);
    }
}

__device__ __forceinline__ void ln_stats(const float (&x)[18], float& mean_r, float& rs) {
    float s = 0.f;
#pragma unroll
    for (int i = 0; i < 18; i++) s += x[i];
#pragma unroll
    for (int o = 16; o; o >>= 1) s += __shfl_xor_sync(0xffffffffu, s, o);
    const float mean = s * (1.0f / 576.0f);
    float q = 0.f;
#pragma unroll
    for (int i = 0; i < 18; i++) { float d = x[i] - mean; q += d * d; }
#pragma unroll
    for (int o = 16; o; o >>= 1) q += __shfl_xor_sync(0xffffffffu, q, o);
    const float var = bfr(q * (1.0f / 576.0f));
    mean_r = bfr(mean);
    rs = __frcp_rn(bfr(sqrtf(bfr(var + 1e-5f))));
}
__device__ __forceinline__ float ln_mod(float x, float mean_r, float rs, float cmul, float sadd) {
    float y = bfr(bfr(x - mean_r) * rs);
    y = bfr(y * bfr(1.0f + cmul));
    return bfr(y + sadd);
}
__device__ __forceinline__ float silu_f(float a) { return __fdividef(a, 1.0f + __expf(-a)); }

__global__ void __launch_bounds__(NTHREADS, 1)
fused_kernel(const __grid_constant__ CUtensorMap tmK, const __grid_constant__ CUtensorMap tmV,
             const __grid_constant__ CUtensorMap tmMod, const __grid_constant__ CUtensorMap tmQ,
             const __grid_constant__ CUtensorMap tmO, const __grid_constant__ CUtensorMap tmG,
             const __grid_constant__ CUtensorMap tmU, const __grid_constant__ CUtensorMap tmD,
             const Params prm) {
    extern __shared__ unsigned char smem_raw[];
    const uint32_t sb = (smem_u32(smem_raw) + 1023u) & ~1023u;
    unsigned char* sp = smem_raw + (sb - smem_u32(smem_raw));
    const int tid = threadIdx.x, warp = tid >> 5, lane = tid & 31;
    const int cta = blockIdx.x;
    const uint32_t bar_full = sb + SM_BAR, bar_empty = sb + SM_BAR + 48, bar_ctrl = sb + SM_BAR + 96;
    const uint32_t bar_sig = sb + SM_BAR + 120;
    volatile int2* meta = reinterpret_cast<volatile int2*>(sp + SM_META);
    volatile unsigned* s_epoch = reinterpret_cast<volatile unsigned*>(sp + SM_EPOCH);

    if (warp == 8) {
        uint64_t pol_ef;
        asm volatile("createpolicy.fractional.L2::evict_first.b64 %0, 1.0;" : "=l"(pol_ef));
        if (lane == 0) {
            for (int i = 0; i < NSLOT; i++) { mbar_init(bar_full + 8 * i, 1); mbar_init(bar_empty + 8 * i, 8); }
            for (int i = 0; i < 4; i++) mbar_init(bar_ctrl + 8 * i, 1);
            asm volatile("fence.mbarrier_init.release.cluster;" ::: "memory");
            asm volatile("fence.proxy.async.shared::cta;" ::: "memory");
            if (cta < 36) {
                mbar_expect_tx(bar_full + 0, 36864);
                for (int i = 0; i < 3; i++) {
                    tma2d(sb + i * 6144, &tmMod, 16 * cta, 192 * i, bar_full + 0);
                    tma2d(sb + 18432 + i * 6144, &tmMod, 576 + 16 * cta, 192 * i, bar_full + 0);
                }
            }
        }
        __syncthreads();
        if (lane == 0) {
            if (cta < NROLE) {
                mbar_expect_tx(bar_full + 8, 36864);
                for (int i = 0; i < 3; i++) tma2d(sb + 36864 + i * 12288, &tmQ, 32 * cta, 192 * i, bar_full + 8);
            } else {
                mbar_arrive(bar_full + 8);
            }
            if (cta >= 36 && cta < 108) {
                mbar_expect_tx(bar_full + 0, 36864);
                const int cA = 1152 + 32 * (cta - 36);
                for (int i = 0; i < 3; i++) {
                    tma2d(sb + i * 6144, &tmMod, cA, 192 * i, bar_full + 0);
                    tma2d(sb + 18432 + i * 6144, &tmMod, cA + 16, 192 * i, bar_full + 0);
                }
            } else if (cta >= 108) {
                mbar_arrive(bar_full + 0);
            }
#define TMA_KV(dst, map, row, bar) tma2d_hint(dst, map, 0, row, bar, pol_ef)
            if (cta < NROLE) {
                mbar_wait(bar_full + 0, 0);
                mbar_wait(bar_full + 8, 0);
                for (int u = 0; u < 2; u++) {
                    const int s = 2 + 2 * u;
                    const int row = (cta * SK + u * UKEYS) * 2;
                    mbar_expect_tx(bar_full + 8 * s, SLOT);
                    TMA_KV(sb + SM_RING + s * SLOT, &tmK, row, bar_full + 8 * s);
                    mbar_expect_tx(bar_full + 8 * (s + 1), SLOT);
                    TMA_KV(sb + SM_RING + (s + 1) * SLOT, &tmV, row, bar_full + 8 * (s + 1));
                    meta[1 + u].x = cta; meta[1 + u].y = 0;
                    mbar_arrive(bar_ctrl + 8 * (1 + u));
                }
            }
        }
        __syncwarp();
        int seq = (cta < NROLE) ? 6 : 2;
        if (cta >= NROLE) mbar_wait(bar_empty + 0, 0);
        else mbar_wait(bar_empty + 0, 0);
        const unsigned epoch = *s_epoch;
        const int par = epoch & 1;
        const unsigned tag32 = epoch + 1u;
        unsigned* ctr = g_ctr[par];
        int cur = (cta < NROLE) ? cta : -1;
        int pslot = 0;
        bool have = false;
        unsigned pf = 0;
        int nunit = 0;
        int wpf = 0;
        auto wprefetch = [&](int i) {
            const unsigned half = (i < 2) ? 18432u : 20736u;
            l2_prefetch(prm.wt[i >> 1] + (size_t)(2 * cta + (i & 1)) * half, half);
        };
        uint4 scan = make_uint4(0, 0, 0, 0);
        while (true) {
            const int s = seq % NSLOT;
            const uint32_t ph = ((seq / NSLOT) & 1) ^ 1;
            mbar_wait(bar_empty + 8 * s, ph);
            int unit = -1;
            while (true) {
                bool fresh = false;
                if (cur < 0) {
                    scan = ldg_relaxed4(ctr + 4 * lane);
                    float best = 0.f; int bestp = -1;
                    const unsigned sv[4] = {scan.x, scan.y, scan.z, scan.w};
#pragma unroll
                    for (int i = 0; i < 4; i++) {
                        const int rem = UNITS - 2 - (int)(sv[i] & 0xffffu);
                        if (rem > 0) {
                            const int p = 4 * lane + i;
                            const float sc = __fdividef((float)rem, (float)((sv[i] >> 16) + 1u)) + 0.001f * (float)((p + cta * 37) & 127);
                            if (sc > best) { best = sc; bestp = p; }
                        }
                    }
#pragma unroll
                    for (int o = 16; o; o >>= 1) {
                        const float ob = __shfl_xor_sync(0xffffffffu, best, o);
                        const int op = __shfl_xor_sync(0xffffffffu, bestp, o);
                        if (ob > best || (ob == best && op > bestp)) { best = ob; bestp = op; }
                    }
                    if (bestp < 0) break;
                    cur = bestp; fresh = true;
                }
                unsigned old = pf;
                if (!have) {
                    if (lane == 0) old = atomicAdd(&ctr[cur], fresh ? 0x10001u : 1u);
                }
                have = false;
                old = __shfl_sync(0xffffffffu, old, 0);
                if (fresh) pslot = (int)(old >> 16) + 1;
                const int tk = (int)(old & 0xffffu) + 2;
                if (tk < UNITS) { unit = tk; break; }
                if (fresh) {
                    unsigned long long* rec = g_part + ((size_t)cur * MAXS + pslot) * PSTRIDE;
                    for (int i = lane; i < 260; i += 32)
                        stg_relaxed64(rec + i, (i == 256 || i == 258) ? 0xff800000u : 0u, tag32);
                }
                cur = -1;
            }
            const int us = (seq >> 1) % 3;
            if (unit < 0) {
                *reinterpret_cast<unsigned*>(sp + SM_NJ + 4 * lane) =
                    (scan.x >> 16) | ((scan.y >> 16) << 8) | ((scan.z >> 16) << 16) | ((scan.w >> 16) << 24);
                __syncwarp();
                if (lane == 0) { meta[us].x = -1; mbar_arrive(bar_ctrl + 8 * us); }
                TS(13);
                break;
            }
            if (lane == 0) {
                const int row = (cur * SK + unit * UKEYS) * 2;
                mbar_expect_tx(bar_full + 8 * s, SLOT);
                TMA_KV(sb + SM_RING + s * SLOT, &tmK, row, bar_full + 8 * s);
                meta[us].x = cur; meta[us].y = pslot;
                mbar_arrive(bar_ctrl + 8 * us);
                if (UNITS - unit > PF_MIN) pf = atomicAdd(&ctr[cur], 1u);
                mbar_wait(bar_empty + 8 * (s + 1), ph);
                mbar_expect_tx(bar_full + 8 * (s + 1), SLOT);
                TMA_KV(sb + SM_RING + (s + 1) * SLOT, &tmV, row, bar_full + 8 * (s + 1));
                if (nunit >= WPF_AT && wpf < 8 && cta < NROLE) { wprefetch(wpf); wpf++; }
            }
            have = (UNITS - unit > PF_MIN);
            seq += 2;
            __syncwarp();
            ++nunit;
            if (cta == 0 && nunit == 8) {
                if (lane == 0) {
                    unsigned spins = 0;
                    while (ldg_relaxed1(&g_started[par]) < gridDim.x) { if (++spins > SPIN_LIMIT) TRAP_AT(__LINE__); }
                    g_started[par ^ 1] = 0;
                    g_epoch = epoch + 1;
                }
                *reinterpret_cast<uint4*>(&g_ctr[par ^ 1][4 * lane]) = make_uint4(0, 0, 0, 0);
            }
        }
        if (cta < NROLE && lane == 0) {
            for (; wpf < 8; wpf++) wprefetch(wpf);
            const int hkv = cta >> 3, ns = cta & 7;
            const int gc = (36 * cta) & ~7;
            for (int i = 0; i < 6; i++) {
                const int sq = seq + i;
                const int s = sq % NSLOT;
                const uint32_t ph = ((sq / NSLOT) & 1) ^ 1;
                const uint32_t dst = sb + SM_RING + s * SLOT;
                const uint32_t fb = bar_full + 8 * s;
                mbar_wait(bar_empty + 8 * s, ph);
                if (i == 0) {
                    mbar_expect_tx(fb, 27648);
                    for (int r = 0; r < 3; r++) tma2d(dst + r * 9216, &tmO, 72 * ns, 256 * hkv + 64 * r, fb);
                } else if (i == 1) {
                    mbar_expect_tx(fb, 9216 + 15360);
                    tma2d(dst, &tmO, 72 * ns, 256 * hkv + 192, fb);
                    mbar_wait(bar_sig, KV_START == 2 ? 1 : 0);
                    tma2d(dst + 9216, &tmG, gc, 0, fb);
                } else if (i == 2) {
                    mbar_expect_tx(fb, 30720);
                    tma2d(dst, &tmU, gc, 0, fb);
                    tma2d(dst + 15360, &tmG, gc, 192, fb);
                } else if (i == 3) {
                    mbar_expect_tx(fb, 30720);
                    tma2d(dst, &tmU, gc, 192, fb);
                    tma2d(dst + 15360, &tmG, gc, 384, fb);
                } else if (i == 4) {
                    mbar_expect_tx(fb, 15360 + 3 * 4608);
                    tma2d(dst, &tmU, gc, 384, fb);
                    for (int r = 0; r < 3; r++) tma2d(dst + 15360 + r * 5120, &tmD, 64 * r, 36 * cta, fb);
                } else {
                    mbar_expect_tx(fb, 6 * 4608);
                    for (int r = 0; r < 6; r++) tma2d(dst + r * 5120, &tmD, 64 * (3 + r), 36 * cta, fb);
                }
            }
        }
        return;
    }

    const int g = lane >> 2, t = lane & 3;
    TS(0);
    unsigned e0 = 0;
    if (tid == 0) e0 = ldg_relaxed1(&g_epoch);
    const uint32_t bufA = sb + SM_BUFA;
    float* s_stat = reinterpret_cast<float*>(sp + SM_STAT);
    unsigned* bufArow = reinterpret_cast<unsigned*>(sp + SM_BUFA + warp * BUFA_PITCH * 2) + lane;
    unsigned cv[9];
    float xh[2] = {0.f, 0.f};
    if (cta < 108) {
        const unsigned* cw = reinterpret_cast<const unsigned*>(prm.c) + warp * 288;
#pragma unroll
        for (int i = 0; i < 9; i++) cv[i] = __ldg(cw + lane + 32 * i);
        if (cta < 36) {
            const unsigned* xw = reinterpret_cast<const unsigned*>(prm.x) + warp * 288;
            float xv[18];
#pragma unroll
            for (int i = 0; i < 9; i++) { unsigned w = __ldg(xw + lane + 32 * i); xv[2 * i] = bf_lo(w); xv[2 * i + 1] = bf_hi(w); }
            if (warp < 2) {
                xh[0] = __bfloat162float(prm.x[(2 * t) * DM + 16 * cta + 8 * warp + g]);
                xh[1] = __bfloat162float(prm.x[(2 * t + 1) * DM + 16 * cta + 8 * warp + g]);
            }
            float mr, rs;
            ln_stats(xv, mr, rs);
            if (lane == 0) { s_stat[2 * warp] = mr; s_stat[2 * warp + 1] = rs; }
        }
#pragma unroll
        for (int i = 0; i < 9; i++) cv[i] = pack_bf2(silu_f(bf_lo(cv[i])), silu_f(bf_hi(cv[i])));
        if (cta < 36) {
#pragma unroll
            for (int i = 0; i < 9; i++) bufArow[32 * i] = cv[i];
        }
    }
    if (tid == 0) {
        *s_epoch = e0;
        atomicAdd(&g_started[e0 & 1], 1u);
    }
    __syncthreads();
    const unsigned epoch = *s_epoch;
    const unsigned tag16 = epoch % 65535u + 1u;
    const unsigned tag2 = epoch % 3u + 1u;
    const unsigned tag32 = epoch + 1u;
    float4* s_red = reinterpret_cast<float4*>(sp + SM_RED);
    const uint32_t bA = bufA + (g * BUFA_PITCH + 2 * t) * 2;
    const int kr = (lane & 7) + 8 * (lane >> 4);
    const int mh = (lane >> 3) & 1;

    auto mod_slice = [&](float4& v) {
        mbar_wait(bar_full + 0, 0);
        TS(18);
        const int tile = warp & 1, kq = warp >> 1;
        float acc[4] = {0.f, 0.f, 0.f, 0.f};
        const uint32_t boxb = sb + mh * 18432;
#pragma unroll
        for (int i = 0; i < 9; i++) {
            const int ks = kq * 9 + i;
            const int r = 16 * ks + kr;
            uint32_t a[4];
            ldsm4t(boxb + r * 32 + ((tile ^ ((r >> 2) & 1)) << 4), a);
            mma16816(acc, a, lds32(bA + ks * 32), lds32(bA + ks * 32 + 16));
        }
        s_red[warp * 32 + lane] = make_float4(acc[0], acc[1], acc[2], acc[3]);
        cons_sync();
        if (warp < 2) {
            v = s_red[warp * 32 + lane];
#pragma unroll
            for (int k = 1; k < 4; k++) { float4 u = s_red[(warp + 2 * k) * 32 + lane]; v.x += u.x; v.y += u.y; v.z += u.z; v.w += u.w; }
        }
    };

    if (cta < 36) {
        TS(17);
        float4 v;
        mod_slice(v);
        if (warp < 2) {
            const int col = 16 * cta + 8 * warp + g;
            const float h0 = ln_mod(xh[0], s_stat[4 * t], s_stat[4 * t + 1], bfr(v.z), bfr(v.x));
            const float h1 = ln_mod(xh[1], s_stat[4 * t + 2], s_stat[4 * t + 3], bfr(v.w), bfr(v.y));
            stg_relaxed1(&g_h[(2 * t) * DM + col], (bf_bits(h0) << 16) | tag16);
            stg_relaxed1(&g_h[(2 * t + 1) * DM + col], (bf_bits(h1) << 16) | tag16);
        }
    }
    TS(1);
    if (cta < NROLE) {
        uint2 hv[9];
        issue_row16(g_h + warp * DM, lane, hv);
        check_row16(g_h + warp * DM, lane, tag16, hv);
        TS(19);
        if (cta < 36) cons_sync();
#pragma unroll
        for (int i = 0; i < 9; i++) bufArow[32 * i] = pack_hi(hv[i].x, hv[i].y);
        cons_sync();
        TS(20);
        mbar_wait(bar_full + 8, 0);
        TS(21);
        const int tile = warp & 1, kq = warp >> 1;
        float acc[4] = {0.f, 0.f, 0.f, 0.f};
        const int ch = 2 * tile + mh;
#pragma unroll
        for (int i = 0; i < 9; i++) {
            const int ks = kq * 9 + i;
            const int r = 16 * ks + kr;
            uint32_t a[4];
            ldsm4t(sb + 36864 + r * 64 + ((ch ^ ((r >> 1) & 3)) << 4), a);
            mma16816(acc, a, lds32(bA + ks * 32), lds32(bA + ks * 32 + 16));
        }
        s_red[warp * 32 + lane] = make_float4(acc[0], acc[1], acc[2], acc[3]);
        cons_sync();
        if (warp < 2) {
            float4 v = s_red[warp * 32 + lane];
#pragma unroll
            for (int k = 1; k < 4; k++) { float4 u = s_red[(warp + 2 * k) * 32 + lane]; v.x += u.x; v.y += u.y; v.z += u.z; v.w += u.w; }
            const int col = 32 * cta + 16 * warp + g;
            stg_relaxed1(&g_q[(2 * t) * 4096 + col], (bf_bits(v.x) << 16) | tag16);
            stg_relaxed1(&g_q[(2 * t + 1) * 4096 + col], (bf_bits(v.y) << 16) | tag16);
            stg_relaxed1(&g_q[(2 * t) * 4096 + col + 8], (bf_bits(v.z) << 16) | tag16);
            stg_relaxed1(&g_q[(2 * t + 1) * 4096 + col + 8], (bf_bits(v.w) << 16) | tag16);
        }
        TS(2);
        if (cta >= 36 && cta < 108) {
#pragma unroll
            for (int i = 0; i < 9; i++) bufArow[32 * i] = cv[i];
            cons_sync();
            float4 v;
            mod_slice(v);
            if (warp < 2) {
                const int colA = 1152 + 32 * (cta - 36) + 8 * warp + g, colB = colA + 16;
                stg_relaxed1(&g_mod[(2 * t) * 3456 + colA], (bf_bits(v.x) << 16) | tag16);
                stg_relaxed1(&g_mod[(2 * t + 1) * 3456 + colA], (bf_bits(v.y) << 16) | tag16);
                stg_relaxed1(&g_mod[(2 * t) * 3456 + colB], (bf_bits(v.z) << 16) | tag16);
                stg_relaxed1(&g_mod[(2 * t + 1) * 3456 + colB], (bf_bits(v.w) << 16) | tag16);
            }
        }
    }
    __syncwarp();
    if (lane == 0) { mbar_arrive(bar_empty + 0); mbar_arrive(bar_empty + 8); }

    int seq = 2;
    {
        uint32_t kpre[2], vpre[2];
        {
            const int key = (lane & 7) + 8 * mh, cs = lane >> 4;
#pragma unroll
            for (int h = 0; h < 2; h++) {
                const int r = 2 * (16 * warp + key) + h;
                kpre[h] = r * 128 + ((cs ^ (r & 7)) << 4);
            }
            const int k8 = (lane & 7), hi = lane >> 4;
            const int vkey = (k8 >> 1) + 8 * (k8 & 1) + 4 * hi;
#pragma unroll
            for (int h = 0; h < 2; h++) {
                const int r = 2 * (16 * warp + vkey) + h;
                vpre[h] = r * 128 + ((mh ^ (r & 7)) << 4);
            }
        }
        uint32_t qf[8][2];
        float o[8][4];
        float m = -INFINITY, l = 0.f;
        int cur = -1, pslot = 0;
        float* scr_o = reinterpret_cast<float*>(sp + SM_SCR);
        float* scr_ml = reinterpret_cast<float*>(sp + SM_ML);
        while (true) {
            const int us = (seq >> 1) % 3;
            const uint32_t cph = (((seq >> 1) - 1) / 3) & 1;
            mbar_wait(bar_ctrl + 8 * us, cph);
            const int np = meta[us].x, nslot = meta[us].y;
            if (np != cur) {
                if (cur >= 0) {
#pragma unroll
                    for (int of = 4; of <= 16; of <<= 1) l += __shfl_xor_sync(0xffffffffu, l, of);
                    if (t == 0) {
#pragma unroll
                        for (int mt = 0; mt < 8; mt++) {
                            scr_o[(warp * 2 + 0) * 128 + 16 * mt + g] = o[mt][0];
                            scr_o[(warp * 2 + 1) * 128 + 16 * mt + g] = o[mt][1];
                            scr_o[(warp * 2 + 0) * 128 + 16 * mt + g + 8] = o[mt][2];
                            scr_o[(warp * 2 + 1) * 128 + 16 * mt + g + 8] = o[mt][3];
                        }
                    }
                    if (lane < 2) { scr_ml[(warp * 2 + lane) * 2] = m; scr_ml[(warp * 2 + lane) * 2 + 1] = l; }
                    cons_sync();
                    {
                        const int h = tid >> 7, d = tid & 127;
                        float M = -INFINITY;
#pragma unroll
                        for (int w = 0; w < 8; w++) M = fmaxf(M, scr_ml[(w * 2 + h) * 2]);
                        float O = 0.f, L = 0.f;
#pragma unroll
                        for (int w = 0; w < 8; w++) {
                            const float f = ex2((scr_ml[(w * 2 + h) * 2] - M) * LOG2E);
                            O += f * scr_o[(w * 2 + h) * 128 + d];
                            L += f * scr_ml[(w * 2 + h) * 2 + 1];
                        }
                        unsigned long long* rec = g_part + ((size_t)cur * MAXS + pslot) * PSTRIDE;
                        stg_relaxed64(rec + tid, __float_as_uint(O), tag32);
                        if (d == 0) {
                            stg_relaxed64(rec + 256 + 2 * h, __float_as_uint(M), tag32);
                            stg_relaxed64(rec + 257 + 2 * h, __float_as_uint(L), tag32);
                        }
                    }
                    cons_sync();
                }
                if (np < 0) break;
                cur = np; pslot = nslot;
                m = -INFINITY; l = 0.f;
#pragma unroll
                for (int mt = 0; mt < 8; mt++) { o[mt][0] = o[mt][1] = o[mt][2] = o[mt][3] = 0.f; }
                const unsigned* qb = g_q + (cur >> 4) * 4096 + (cur & 15) * 256 + (g & 1) * 128 + 2 * t;
                unsigned spins = 0;
                while (true) {
                    bool ok = true;
#pragma unroll
                    for (int ks = 0; ks < 8; ks++) {
                        uint2 a = ldg_relaxed2(qb + 16 * ks), b = ldg_relaxed2(qb + 16 * ks + 8);
                        ok = ok && ((a.x & 0xffffu) == tag16) && ((a.y & 0xffffu) == tag16) &&
                             ((b.x & 0xffffu) == tag16) && ((b.y & 0xffffu) == tag16);
                        qf[ks][0] = pack_hi(a.x, a.y);
                        qf[ks][1] = pack_hi(b.x, b.y);
                    }
                    if (__all_sync(0xffffffffu, ok)) break;
                    if (++spins > SPIN_LIMIT) TRAP_AT(__LINE__);
                }
            }
            if (seq == 2) TS(3);
            if (seq == 6) TS(4);
            const int sK = seq % NSLOT;
            const uint32_t ph = (seq / NSLOT) & 1;
            const uint32_t kb = sb + SM_RING + sK * SLOT, vb = kb + SLOT;
            mbar_wait(bar_full + 8 * sK, ph);
            float c0[4] = {0.f, 0.f, 0.f, 0.f}, c1[4] = {0.f, 0.f, 0.f, 0.f};
#pragma unroll
            for (int ks = 0; ks < 8; ks += 2) {
                uint32_t a[4], b[4];
                ldsm4(kb + (kpre[ks >> 2] ^ ((ks & 3) << 5)), a);
                ldsm4(kb + (kpre[(ks + 1) >> 2] ^ (((ks + 1) & 3) << 5)), b);
                mma16816(c0, a, qf[ks][0], qf[ks][1]);
                mma16816(c1, b, qf[ks + 1][0], qf[ks + 1][1]);
            }
            __syncwarp();
            if (lane == 0) mbar_arrive(bar_empty + 8 * sK);
            float s0 = (t & 1) ? (c0[1] + c1[1]) : (c0[0] + c1[0]);
            float s1 = (t & 1) ? (c0[3] + c1[3]) : (c0[2] + c1[2]);
            s0 = bfr(bfr(s0) * QSCALE);
            s1 = bfr(bfr(s1) * QSCALE);
            float bm = fmaxf(s0, s1);
            if (__any_sync(0xffffffffu, bm > m)) {
#pragma unroll
                for (int of = 4; of <= 16; of <<= 1) bm = fmaxf(bm, __shfl_xor_sync(0xffffffffu, bm, of));
                const float mn = fmaxf(m, bm);
                const float al = ex2((m - mn) * LOG2E);
                m = mn; l *= al;
                const float alo = __shfl_xor_sync(0xffffffffu, al, 1);
                const float a0 = (t & 1) ? alo : al, a1 = (t & 1) ? al : alo;
#pragma unroll
                for (int mt = 0; mt < 8; mt++) { o[mt][0] *= a0; o[mt][1] *= a1; o[mt][2] *= a0; o[mt][3] *= a1; }
            }
            const float p0 = ex2((s0 - m) * LOG2E), p1 = ex2((s1 - m) * LOG2E);
            l += p0 + p1;
            const unsigned pk = pack_bf2(p0, p1);
            const unsigned pb0 = __shfl_sync(0xffffffffu, pk, 4 * t + (g & 1));
            const unsigned pb1 = __shfl_sync(0xffffffffu, pk, 4 * (t + 4) + (g & 1));
            mbar_wait(bar_full + 8 * (sK + 1), ph);
#pragma unroll
            for (int mt = 0; mt < 8; mt++) {
                uint32_t a[4];
                ldsm4t(vb + (vpre[mt >> 2] ^ ((mt & 3) << 5)), a);
                mma16816(o[mt], a, pb0, pb1);
            }
            __syncwarp();
            if (lane == 0) mbar_arrive(bar_empty + 8 * (sK + 1));
            seq += 2;
        }
    }
    TS(5);
    if (tid == 0) TSV(16, seq);
    if (cta >= NROLE) return;
    if (tid == 0) mbar_arrive(bar_sig);

    const int hkv = cta >> 3, ns = cta & 7;
    uint2 cbv[9], sbv[9];
    const unsigned* cbp = g_mod + warp * 3456 + 4 * DM;
    const unsigned* sbp = g_mod + warp * 3456 + 3 * DM;
    issue_row16(cbp, lane, cbv);
    issue_row16(sbp, lane, sbv);
    const int src = lane & 15, ch3 = 2 * warp + (lane >> 4);
    const int v0 = ns * 576 + 36 * hkv + 4 * ch3;
    const bool t3act = (warp < 4 || (warp == 4 && lane < 16));
    const int col3 = (v0 + (src & 3)) >> 3, b3 = (v0 + (src & 3)) & 7;
    float x3 = 0.f; unsigned gaw = 0;
    if (t3act && src < 4) {
        x3 = __bfloat162float(prm.x[b3 * DM + col3]);
        gaw = ldg_relaxed1(&g_mod[b3 * 3456 + 2 * DM + col3]);
    }
    unsigned gbw = 0;
    const int col5 = 8 * cta + (tid >> 3), b5 = tid & 7;
    if (cta < 72 && tid < 64) gbw = ldg_relaxed1(&g_mod[b5 * 3456 + 5 * DM + col5]);
    {
        const int p = warp * HKV + hkv;
        const unsigned nj = (unsigned)sp[SM_NJ + p] + 1u;
        const unsigned long long* rec = g_part + (size_t)p * MAXS * PSTRIDE;
        float M0 = -INFINITY, M1 = -INFINITY, L0 = 0.f, L1 = 0.f;
        float O[8];
#pragma unroll
        for (int i = 0; i < 8; i++) O[i] = 0.f;
        for (unsigned s = 0; s < nj; s += 2) {
            const bool two = s + 1 < nj;
            const unsigned long long* r0 = rec + (size_t)s * PSTRIDE;
            const unsigned long long* r1 = two ? r0 + PSTRIDE : r0;
            ulonglong2 a[6], b[6];
            unsigned spins = 0;
            while (true) {
#pragma unroll
                for (int j = 0; j < 4; j++) a[j] = ldg_relaxed2x64(r0 + 2 * (32 * j + lane));
                a[4] = ldg_relaxed2x64(r0 + 256); a[5] = ldg_relaxed2x64(r0 + 258);
#pragma unroll
                for (int j = 0; j < 4; j++) b[j] = ldg_relaxed2x64(r1 + 2 * (32 * j + lane));
                b[4] = ldg_relaxed2x64(r1 + 256); b[5] = ldg_relaxed2x64(r1 + 258);
                bool ok = true;
#pragma unroll
                for (int j = 0; j < 6; j++)
                    ok = ok && (unsigned)(a[j].x >> 32) == tag32 && (unsigned)(a[j].y >> 32) == tag32 &&
                         (unsigned)(b[j].x >> 32) == tag32 && (unsigned)(b[j].y >> 32) == tag32;
                if (ok) break;
                if (++spins > SPIN_LIMIT) TRAP_AT(__LINE__);
            }
#pragma unroll
            for (int q = 0; q < 2; q++) {
                if (q == 1 && !two) break;
                const ulonglong2* r = q ? b : a;
                const float m0 = __uint_as_float((unsigned)r[4].x), l0 = __uint_as_float((unsigned)r[4].y);
                const float m1 = __uint_as_float((unsigned)r[5].x), l1 = __uint_as_float((unsigned)r[5].y);
                const float N0 = fmaxf(M0, m0), N1 = fmaxf(M1, m1);
                const float fo0 = ex2((M0 - N0) * LOG2E), fn0 = ex2((m0 - N0) * LOG2E);
                const float fo1 = ex2((M1 - N1) * LOG2E), fn1 = ex2((m1 - N1) * LOG2E);
                M0 = N0; M1 = N1;
                L0 = L0 * fo0 + l0 * fn0; L1 = L1 * fo1 + l1 * fn1;
#pragma unroll
                for (int j = 0; j < 4; j++) {
                    const float fo = j < 2 ? fo0 : fo1, fn = j < 2 ? fn0 : fn1;
                    O[2 * j] = O[2 * j] * fo + __uint_as_float((unsigned)r[j].x) * fn;
                    O[2 * j + 1] = O[2 * j + 1] * fo + __uint_as_float((unsigned)r[j].y) * fn;
                }
            }
        }
        const float i0 = __frcp_rn(L0), i1 = __frcp_rn(L1);
        unsigned* ob = reinterpret_cast<unsigned*>(sp + SM_SCR + warp * BUFO_PITCH * 2) + lane;
#pragma unroll
        for (int j = 0; j < 4; j++) {
            const float iv = j < 2 ? i0 : i1;
            ob[32 * j] = pack_bf2(O[2 * j] * iv, O[2 * j + 1] * iv);
        }
    }
    cons_sync();
    TS(6);
    if (warp < 5) {
        const int s0 = seq % NSLOT, s1 = (seq + 1) % NSLOT;
        mbar_wait(bar_full + 8 * s0, (seq / NSLOT) & 1);
        const uint32_t w0 = sb + SM_RING + s0 * SLOT, w1 = sb + SM_RING + s1 * SLOT;
        const uint32_t bO = sb + SM_SCR + (g * BUFO_PITCH + 2 * t) * 2;
        int cb = 16 * warp + 8 * mh;
        if (cb > 64) cb = 64;
        float acc[2][4] = {{0.f, 0.f, 0.f, 0.f}, {0.f, 0.f, 0.f, 0.f}};
#pragma unroll
        for (int ks = 0; ks < 16; ks++) {
            if (ks == 12) mbar_wait(bar_full + 8 * s1, ((seq + 1) / NSLOT) & 1);
            const int r = 16 * ks + kr;
            const uint32_t addr = (ks < 12 ? w0 + r * 144 : w1 + (r - 192) * 144) + cb * 2;
            uint32_t a[4];
            ldsm4t(addr, a);
            mma16816(acc[ks & 1], a, lds32(bO + ks * 32), lds32(bO + ks * 32 + 16));
        }
        unsigned* dst = g_wop + (size_t)hkv * (DM * NB) + (72 * ns + 16 * warp + g) * 8 + 2 * t;
        stg_relaxed2(dst, (__float_as_uint(acc[0][0] + acc[1][0]) & ~3u) | tag2, (__float_as_uint(acc[0][1] + acc[1][1]) & ~3u) | tag2);
        if (warp < 4)
            stg_relaxed2(dst + 64, (__float_as_uint(acc[0][2] + acc[1][2]) & ~3u) | tag2, (__float_as_uint(acc[0][3] + acc[1][3]) & ~3u) | tag2);
    }
    TS(7);
    if (t3act) {
        const unsigned amask = warp < 4 ? 0xffffffffu : 0x0000ffffu;
        const unsigned* ptr = g_wop + (size_t)src * (DM * NB) + v0;
        uint4 v;
        unsigned spins = 0;
        while (true) {
            v = ldg_relaxed4(ptr);
            if ((v.x & 3u) == tag2 && (v.y & 3u) == tag2 && (v.z & 3u) == tag2 && (v.w & 3u) == tag2) break;
            if (++spins > SPIN_LIMIT) TRAP_AT(__LINE__);
        }
        float f0 = __uint_as_float(v.x & ~3u), f1 = __uint_as_float(v.y & ~3u), f2 = __uint_as_float(v.z & ~3u), f3 = __uint_as_float(v.w & ~3u);
#pragma unroll
        for (int of = 1; of <= 8; of <<= 1) {
            f0 += __shfl_xor_sync(amask, f0, of); f1 += __shfl_xor_sync(amask, f1, of);
            f2 += __shfl_xor_sync(amask, f2, of); f3 += __shfl_xor_sync(amask, f3, of);
        }
        if (src < 4) {
            spins = 0;
            while ((gaw & 0xffffu) != tag16) {
                gaw = ldg_relaxed1(&g_mod[b3 * 3456 + 2 * DM + col3]);
                if (++spins > SPIN_LIMIT) TRAP_AT(__LINE__);
            }
            const float a = bfr(src == 0 ? f0 : src == 1 ? f1 : src == 2 ? f2 : f3);
            const float x2 = x3 + bfr(bf_hi(gaw) * a);
            stg_relaxed1(&g_x2[b3 * DM + col3], (bf_bits(x2) << 16) | tag16);
        }
    }
    TS(8);
    {
        uint2 xv2[9];
        issue_row16(g_x2 + warp * DM, lane, xv2);
        check_row16(cbp, lane, tag16, cbv);
        check_row16(sbp, lane, tag16, sbv);
        check_row16(g_x2 + warp * DM, lane, tag16, xv2);
        float xf[18];
#pragma unroll
        for (int i = 0; i < 9; i++) { xf[2 * i] = bf_hi(xv2[i].x); xf[2 * i + 1] = bf_hi(xv2[i].y); }
        float mr, rs;
        ln_stats(xf, mr, rs);
#pragma unroll
        for (int i = 0; i < 9; i++) {
            const float h0 = ln_mod(xf[2 * i], mr, rs, bf_hi(cbv[i].x), bf_hi(sbv[i].x));
            const float h1 = ln_mod(xf[2 * i + 1], mr, rs, bf_hi(cbv[i].y), bf_hi(sbv[i].y));
            bufArow[32 * i] = pack_bf2(h0, h1);
        }
        if (tid < 48) *reinterpret_cast<unsigned*>(sp + SM_ACT + ((tid / 6) * ACT_PITCH + 36 + 2 * (tid % 6)) * 2) = 0;
    }
    cons_sync();
    TS(9);
    unsigned x2w = 0;
    if (cta < 72 && tid < 64) x2w = ldg_relaxed1(&g_x2[b5 * DM + col5]);
    if (warp < 5) {
        uint32_t sl[4];
#pragma unroll
        for (int i = 0; i < 4; i++) {
            const int sq = seq + 1 + i;
            mbar_wait(bar_full + 8 * (sq % NSLOT), (sq / NSLOT) & 1);
            sl[i] = sb + SM_RING + (sq % NSLOT) * SLOT;
        }
        uint32_t base[3];
        base[0] = mh ? sl[1] : sl[0] + 9216;
        base[1] = mh ? sl[2] : sl[1] + 15360;
        base[2] = mh ? sl[3] : sl[2] + 15360;
        float acc[4][4];
#pragma unroll
        for (int i = 0; i < 4; i++) acc[i][0] = acc[i][1] = acc[i][2] = acc[i][3] = 0.f;
#pragma unroll
        for (int ks = 0; ks < 36; ks++) {
            const int r = (16 * ks) % 192 + kr;
            uint32_t a[4];
            ldsm4t(base[ks / 12] + r * 80 + warp * 16, a);
            mma16816(acc[ks & 3], a, lds32(bA + ks * 32), lds32(bA + ks * 32 + 16));
        }
        const int cl = 8 * warp + g - 4 * (cta & 1);
#pragma unroll
        for (int e = 0; e < 2; e++) {
            const float gt = bfr(acc[0][e] + acc[1][e] + acc[2][e] + acc[3][e]);
            const float up = bfr(acc[0][2 + e] + acc[1][2 + e] + acc[2][2 + e] + acc[3][2 + e]);
            const float u2 = 1.5957691216057308f * (gt + 0.044715f * gt * gt * gt);
            const float ge = bfr(__fdividef(gt, 1.0f + __expf(-u2)));
            if (cl >= 0 && cl < 36)
                *reinterpret_cast<__nv_bfloat16*>(sp + SM_ACT + ((2 * t + e) * ACT_PITCH + cl) * 2) = __float2bfloat16_rn(ge * up);
        }
    }
    cons_sync();
    TS(10);
    {
        const int s4 = (seq + 4) % NSLOT, s5 = (seq + 5) % NSLOT;
        mbar_wait(bar_full + 8 * s4, ((seq + 4) / NSLOT) & 1);
        mbar_wait(bar_full + 8 * s5, ((seq + 5) / NSLOT) & 1);
        const uint32_t d4 = sb + SM_RING + s4 * SLOT + 15360, d5 = sb + SM_RING + s5 * SLOT;
        const uint32_t bAct = sb + SM_ACT + (g * ACT_PITCH + 2 * t) * 2;
        uint32_t bf[3][2];
#pragma unroll
        for (int ks = 0; ks < 3; ks++) { bf[ks][0] = lds32(bAct + ks * 32); bf[ks][1] = lds32(bAct + ks * 32 + 16); }
        for (int tile = warp; tile < 36; tile += 8) {
            const int cbk = tile >> 2;
            const uint32_t box = cbk < 3 ? d4 + cbk * 5120 : d5 + (cbk - 3) * 5120;
            const int ch = (tile & 3) * 2 + mh;
            float acc[4] = {0.f, 0.f, 0.f, 0.f};
#pragma unroll
            for (int ks = 0; ks < 3; ks++) {
                int r = 16 * ks + kr;
                if (r > 35) r = 35;
                uint32_t a[4];
                ldsm4t(box + r * 128 + ((ch ^ (r & 7)) << 4), a);
                mma16816(acc, a, bf[ks][0], bf[ks][1]);
            }
            unsigned* dst = g_dnp + (size_t)cta * (DM * NB) + (16 * tile + g) * 8 + 2 * t;
            stg_relaxed2(dst, (__float_as_uint(acc[0]) & ~3u) | tag2, (__float_as_uint(acc[1]) & ~3u) | tag2);
            stg_relaxed2(dst + 64, (__float_as_uint(acc[2]) & ~3u) | tag2, (__float_as_uint(acc[3]) & ~3u) | tag2);
        }
    }
    TS(11);
    if (cta < 72) {
        const int ch = lane & 15, sl = lane >> 4;
        const unsigned* ptr = g_dnp + (size_t)(16 * warp + sl) * (DM * NB) + 64 * cta + 4 * ch;
        uint4 v[8];
#pragma unroll
        for (int i = 0; i < 8; i++) v[i] = ldg_relaxed4(ptr + (size_t)(2 * i) * (DM * NB));
        unsigned spins = 0;
        while (true) {
            bool ok = true;
#pragma unroll
            for (int i = 0; i < 8; i++) {
                if ((v[i].x & 3u) != tag2 || (v[i].y & 3u) != tag2 || (v[i].z & 3u) != tag2 || (v[i].w & 3u) != tag2) {
                    v[i] = ldg_relaxed4(ptr + (size_t)(2 * i) * (DM * NB));
                    ok = false;
                }
            }
            if (ok) break;
            if (++spins > SPIN_LIMIT) TRAP_AT(__LINE__);
        }
        float f[4] = {0.f, 0.f, 0.f, 0.f};
#pragma unroll
        for (int i = 0; i < 8; i++) {
            f[0] += __uint_as_float(v[i].x & ~3u); f[1] += __uint_as_float(v[i].y & ~3u);
            f[2] += __uint_as_float(v[i].z & ~3u); f[3] += __uint_as_float(v[i].w & ~3u);
        }
#pragma unroll
        for (int e = 0; e < 4; e++) f[e] += __shfl_xor_sync(0xffffffffu, f[e], 16);
        if (lane < 16) s_red[warp * 16 + ch] = make_float4(f[0], f[1], f[2], f[3]);
        cons_sync();
        if (tid < 64) {
            spins = 0;
            while ((gbw & 0xffffu) != tag16) {
                gbw = ldg_relaxed1(&g_mod[b5 * 3456 + 5 * DM + col5]);
                if (++spins > SPIN_LIMIT) TRAP_AT(__LINE__);
            }
            const float* r = reinterpret_cast<const float*>(s_red);
            float s = 0.f;
#pragma unroll
            for (int w = 0; w < 8; w++) s += r[w * 64 + tid];
            const float o = bf_hi(x2w) + bfr(bf_hi(gbw) * bfr(s));
            prm.out[b5 * DM + col5] = __float2bfloat16_rn(o);
        }
        TS(12);
    }
}

typedef CUresult (*EncodeFn)(CUtensorMap*, CUtensorMapDataType, cuuint32_t, void*, const cuuint64_t*, const cuuint64_t*,
                             const cuuint32_t*, const cuuint32_t*, CUtensorMapInterleave, CUtensorMapSwizzle,
                             CUtensorMapL2promotion, CUtensorMapFloatOOBfill);

bool make_map(EncodeFn fn, CUtensorMap* m, const void* ptr, uint64_t inner, uint64_t outer, uint64_t stride_bytes,
              uint32_t box_inner, uint32_t box_outer, CUtensorMapSwizzle sw, CUtensorMapL2promotion promo) {
    cuuint64_t dims[2] = {inner, outer};
    cuuint64_t strides[1] = {stride_bytes};
    cuuint32_t box[2] = {box_inner, box_outer};
    cuuint32_t es[2] = {1, 1};
    return fn(m, CU_TENSOR_MAP_DATA_TYPE_BFLOAT16, 2, const_cast<void*>(ptr), dims, strides, box, es,
              CU_TENSOR_MAP_INTERLEAVE_NONE, sw, promo, CU_TENSOR_MAP_FLOAT_OOB_FILL_NONE) == CUDA_SUCCESS;
}

}

extern "C" void kernel_launch(void* const* d_in, const int* in_sizes, int n_in, void* d_out, int out_size) {
    (void)in_sizes; (void)n_in; (void)out_size;
    static EncodeFn encode = nullptr;
    static int num_sms = 0;
    if (!encode) {
        void* fn = nullptr;
        cudaDriverEntryPointQueryResult qres;
        cudaGetDriverEntryPoint("cuTensorMapEncodeTiled", &fn, cudaEnableDefault, &qres);
        encode = (EncodeFn)fn;
        int dev = 0;
        cudaGetDevice(&dev);
        cudaDeviceGetAttribute(&num_sms, cudaDevAttrMultiProcessorCount, dev);
        cudaFuncSetAttribute(fused_kernel, cudaFuncAttributeMaxDynamicSharedMemorySize, SMEM_BYTES);
    }
    CUtensorMap tmK, tmV, tmMod, tmQ, tmO, tmG, tmU, tmD;
    const uint64_t kvrows = (uint64_t)NB * HKV * SK * 2;
    make_map(encode, &tmK, d_in[1], 64, kvrows, 128, 64, 256, CU_TENSOR_MAP_SWIZZLE_128B, CU_TENSOR_MAP_L2_PROMOTION_L2_256B);
    make_map(encode, &tmV, d_in[2], 64, kvrows, 128, 64, 256, CU_TENSOR_MAP_SWIZZLE_128B, CU_TENSOR_MAP_L2_PROMOTION_L2_256B);
    make_map(encode, &tmQ, d_in[3], 4096, DM, 8192, 32, 192, CU_TENSOR_MAP_SWIZZLE_64B, CU_TENSOR_MAP_L2_PROMOTION_L2_128B);
    make_map(encode, &tmO, d_in[4], DM, 4096, DM * 2, 72, 64, CU_TENSOR_MAP_SWIZZLE_NONE, CU_TENSOR_MAP_L2_PROMOTION_L2_128B);
    make_map(encode, &tmG, d_in[6], FF, DM, FF * 2, 40, 192, CU_TENSOR_MAP_SWIZZLE_NONE, CU_TENSOR_MAP_L2_PROMOTION_L2_128B);
    make_map(encode, &tmU, d_in[7], FF, DM, FF * 2, 40, 192, CU_TENSOR_MAP_SWIZZLE_NONE, CU_TENSOR_MAP_L2_PROMOTION_L2_128B);
    make_map(encode, &tmD, d_in[8], DM, FF, DM * 2, 64, 36, CU_TENSOR_MAP_SWIZZLE_128B, CU_TENSOR_MAP_L2_PROMOTION_L2_128B);
    make_map(encode, &tmMod, d_in[10], 6 * DM, DM, 6 * DM * 2, 16, 192, CU_TENSOR_MAP_SWIZZLE_32B, CU_TENSOR_MAP_L2_PROMOTION_L2_128B);
    Params prm;
    prm.x = (const __nv_bfloat16*)d_in[0];
    prm.c = (const __nv_bfloat16*)d_in[9];
    prm.wt[0] = (const unsigned char*)d_in[4];
    prm.wt[1] = (const unsigned char*)d_in[6];
    prm.wt[2] = (const unsigned char*)d_in[7];
    prm.wt[3] = (const unsigned char*)d_in[8];
    prm.out = (__nv_bfloat16*)d_out;
    int grid = num_sms < MAXCTA ? num_sms : MAXCTA;
    fused_kernel<<<grid, NTHREADS, SMEM_BYTES>>>(tmK, tmV, tmMod, tmQ, tmO, tmG, tmU, tmD, prm);
}
```

```cpp
#include <cuda_runtime.h>
#include <cuda_bf16.h>
#include <cuda.h>
#include <stdint.h>

namespace {

constexpr int NB = 8;
constexpr int DM = 576;
constexpr int HKV = 16;
constexpr int SK = 8192;
constexpr int DH = 128;
constexpr int FF = 4608;
constexpr int NPAIR = NB * HKV;
constexpr int UKEYS = 64;
constexpr int UNITS = SK / UKEYS;
constexpr int U0 = 4;
constexpr int TILE = 16384;
constexpr int NTILE = 8;
#define INFL 4
#define TINFL 2
#define WSTART 6
constexpr int NROLE = 128;
constexpr int MAXCTA = 132;
constexpr int MAXREC = 2 * (MAXCTA + 1);
constexpr int RSTRIDE = 272;
constexpr int NTHREADS = 320;

constexpr int SM_RING = 0;
constexpr int SM_WREG = NTILE * TILE;
constexpr int SM_WB = SM_WREG + 36864;
constexpr int SM_BUFA = SM_WREG + 82944;
constexpr int BUFA_PITCH = 584;
constexpr int SM_RED = SM_BUFA + 8 * BUFA_PITCH * 2;
constexpr int SM_ACT = SM_RED + 4096;
constexpr int ACT_PITCH = 56;
constexpr int SM_ML = SM_ACT + 8 * ACT_PITCH * 2;
constexpr int SM_STAT = SM_ML + 128;
constexpr int SM_META = SM_STAT + 64;
constexpr int SM_BAR = SM_META + 32;
constexpr int SM_EPOCH = SM_BAR + 24 * 8;
constexpr int SM_TOTAL = SM_EPOCH + 16;
constexpr int SMEM_BYTES = SM_TOTAL + 1024;

__device__ __align__(16) unsigned g_ctr[2][NPAIR];
__device__ unsigned g_epoch;
__device__ unsigned g_started[2];
__device__ __align__(16) unsigned g_h[NB * DM];
__device__ __align__(16) unsigned g_mod[NB * 6 * DM];
__device__ __align__(16) unsigned g_q[NB * 4096];
__device__ __align__(128) unsigned long long g_part[(size_t)MAXREC * NPAIR * RSTRIDE];
__device__ __align__(16) unsigned g_wop[(size_t)NROLE * DM * NB];
__device__ __align__(16) unsigned g_x2[NB * DM];
__device__ __align__(16) unsigned g_dnp[(size_t)NROLE * DM * NB];

struct Params {
    const __nv_bfloat16* x;
    const __nv_bfloat16* c;
    __nv_bfloat16* out;
};

#define TRAP_AT(line) __trap()
#define TS(i)
#define TS2(i)
#define TSP(i)
#define TSG(i, thr)
#define TSV(i, v)

__device__ __forceinline__ uint32_t smem_u32(const void* p) { return (uint32_t)__cvta_generic_to_shared(p); }
__device__ __forceinline__ void mbar_init(uint32_t bar, uint32_t cnt) {
    asm volatile("mbarrier.init.shared::cta.b64 [%0], %1;" ::"r"(bar), "r"(cnt) : "memory");
}
__device__ __forceinline__ void mbar_expect_tx(uint32_t bar, uint32_t bytes) {
    asm volatile("mbarrier.arrive.expect_tx.shared::cta.b64 _, [%0], %1;" ::"r"(bar), "r"(bytes) : "memory");
}
__device__ __forceinline__ void mbar_arrive(uint32_t bar) {
    asm volatile("mbarrier.arrive.shared::cta.b64 _, [%0];" ::"r"(bar) : "memory");
}
__device__ __forceinline__ bool mbar_try(uint32_t bar, uint32_t parity) {
    uint32_t ok;
    asm volatile(
        "{\n.reg .pred p;\n"
        "mbarrier.try_wait.parity.shared::cta.b64 p, [%1], %2;\n"
        "selp.u32 %0, 1, 0, p;\n}\n"
        : "=r"(ok) : "r"(bar), "r"(parity) : "memory");
    return ok != 0;
}
__device__ __noinline__ void mbar_wait_slow(uint32_t bar, uint32_t parity) {
    unsigned long long t0, t1;
    asm volatile("mov.u64 %0, %globaltimer;" : "=l"(t0));
    while (!mbar_try(bar, parity)) {
        asm volatile("mov.u64 %0, %globaltimer;" : "=l"(t1));
        if (t1 - t0 > 2000000000ull) TRAP_AT(__LINE__);
    }
}
__device__ __forceinline__ void mbar_wait(uint32_t bar, uint32_t parity) {
    if (!mbar_try(bar, parity)) mbar_wait_slow(bar, parity);
}
__device__ __forceinline__ void tma2d(uint32_t dst, const CUtensorMap* map, int c0, int c1, uint32_t bar) {
    asm volatile(
        "cp.async.bulk.tensor.2d.shared::cluster.global.mbarrier::complete_tx::bytes [%0], [%1, {%3, %4}], [%2];"
        ::"r"(dst), "l"((uint64_t)map), "r"(bar), "r"(c0), "r"(c1) : "memory");
}
__device__ __forceinline__ void prefetch_map(const CUtensorMap* map) {
    asm volatile("prefetch.tensormap [%0];" ::"l"((uint64_t)map) : "memory");
}
__device__ __forceinline__ void ldsm4(uint32_t addr, uint32_t (&r)[4]) {
    asm volatile("ldmatrix.sync.aligned.m8n8.x4.shared.b16 {%0,%1,%2,%3}, [%4];"
                 : "=r"(r[0]), "=r"(r[1]), "=r"(r[2]), "=r"(r[3]) : "r"(addr) : "memory");
}
__device__ __forceinline__ void ldsm4t(uint32_t addr, uint32_t (&r)[4]) {
    asm volatile("ldmatrix.sync.aligned.m8n8.x4.trans.shared.b16 {%0,%1,%2,%3}, [%4];"
                 : "=r"(r[0]), "=r"(r[1]), "=r"(r[2]), "=r"(r[3]) : "r"(addr) : "memory");
}
__device__ __forceinline__ void mma16816(float (&c)[4], const uint32_t (&a)[4], uint32_t b0, uint32_t b1) {
    asm volatile(
        "mma.sync.aligned.m16n8k16.row.col.f32.bf16.bf16.f32 {%0,%1,%2,%3}, {%4,%5,%6,%7}, {%8,%9}, {%0,%1,%2,%3};"
        : "+f"(c[0]), "+f"(c[1]), "+f"(c[2]), "+f"(c[3])
        : "r"(a[0]), "r"(a[1]), "r"(a[2]), "r"(a[3]), "r"(b0), "r"(b1));
}
__device__ __forceinline__ void cons_sync() { asm volatile("bar.sync 1, 256;" ::: "memory"); }
__device__ __forceinline__ void group_sync(int grp) { asm volatile("bar.sync %0, 128;" ::"r"(2 + grp) : "memory"); }
__device__ __forceinline__ uint32_t lds32(uint32_t addr) {
    uint32_t v; asm volatile("ld.shared.u32 %0, [%1];" : "=r"(v) : "r"(addr) : "memory"); return v;
}
__device__ __forceinline__ uint2 ldg_relaxed2(const unsigned* p) {
    uint2 v; asm volatile("ld.relaxed.gpu.global.v2.u32 {%0,%1}, [%2];" : "=r"(v.x), "=r"(v.y) : "l"(p) : "memory"); return v;
}
__device__ __forceinline__ uint4 ldg_relaxed4(const unsigned* p) {
    uint4 v; asm volatile("ld.relaxed.gpu.global.v4.u32 {%0,%1,%2,%3}, [%4];"
                          : "=r"(v.x), "=r"(v.y), "=r"(v.z), "=r"(v.w) : "l"(p) : "memory"); return v;
}
__device__ __forceinline__ unsigned ldg_relaxed1(const unsigned* p) {
    unsigned v; asm volatile("ld.relaxed.gpu.global.u32 %0, [%1];" : "=r"(v) : "l"(p) : "memory"); return v;
}
__device__ __forceinline__ unsigned long long ldg_relaxed64(const unsigned long long* p) {
    unsigned long long v; asm volatile("ld.relaxed.gpu.global.u64 %0, [%1];" : "=l"(v) : "l"(p) : "memory"); return v;
}
__device__ __forceinline__ ulonglong2 ldg_relaxed64x2(const unsigned long long* p) {
    ulonglong2 v; asm volatile("ld.relaxed.gpu.global.v2.u64 {%0,%1}, [%2];" : "=l"(v.x), "=l"(v.y) : "l"(p) : "memory"); return v;
}
__device__ __forceinline__ void stg_relaxed1(unsigned* p, unsigned v) {
    asm volatile("st.relaxed.gpu.global.u32 [%0], %1;" ::"l"(p), "r"(v) : "memory");
}
__device__ __forceinline__ void stg_relaxed2(unsigned* p, unsigned a, unsigned b) {
    asm volatile("st.relaxed.gpu.global.v2.u32 [%0], {%1,%2};" ::"l"(p), "r"(a), "r"(b) : "memory");
}
__device__ __forceinline__ void stg_relaxed64(unsigned long long* p, float v, unsigned tag) {
    const unsigned long long w = ((unsigned long long)__float_as_uint(v) << 32) | tag;
    asm volatile("st.relaxed.gpu.global.u64 [%0], %1;" ::"l"(p), "l"(w) : "memory");
}
__device__ __forceinline__ unsigned atom_add_lane0(unsigned* p, unsigned inc, int lane) {
    unsigned v = 0;
    asm volatile("{\n.reg .pred p;\nsetp.eq.s32 p, %3, 0;\n@p atom.relaxed.gpu.global.add.u32 %0, [%1], %2;\n}\n"
                 : "+r"(v) : "l"(p), "r"(inc), "r"(lane) : "memory");
    return v;
}
__device__ __forceinline__ float ex2(float x) { float y; asm("ex2.approx.ftz.f32 %0, %1;" : "=f"(y) : "f"(x)); return y; }

__device__ __forceinline__ void cons_sync_p(unsigned live) {
    asm volatile("{\n.reg .pred p;\nsetp.ne.u32 p, %0, 0;\n@p bar.sync 1, 256;\n}\n" ::"r"(live) : "memory");
}
__device__ __forceinline__ void group_sync_p(int grp, unsigned live) {
    asm volatile("{\n.reg .pred p;\nsetp.ne.u32 p, %1, 0;\n@p bar.sync %0, 128;\n}\n" ::"r"(2 + grp), "r"(live) : "memory");
}
__device__ __forceinline__ void ldg_relaxed1_p(unsigned& v, const unsigned* p, unsigned live) {
    asm volatile("{\n.reg .pred p;\nsetp.ne.u32 p, %2, 0;\n@p ld.relaxed.gpu.global.u32 %0, [%1];\n}\n" : "+r"(v) : "l"(p), "r"(live) : "memory");
}
__device__ __forceinline__ void ldg_relaxed2_p(uint2& v, const unsigned* p, unsigned live) {
    asm volatile("{\n.reg .pred p;\nsetp.ne.u32 p, %3, 0;\n@p ld.relaxed.gpu.global.v2.u32 {%0,%1}, [%2];\n}\n"
                 : "+r"(v.x), "+r"(v.y) : "l"(p), "r"(live) : "memory");
}
__device__ __forceinline__ void ldg_relaxed4_p(uint4& v, const unsigned* p, unsigned live) {
    asm volatile("{\n.reg .pred p;\nsetp.ne.u32 p, %5, 0;\n@p ld.relaxed.gpu.global.v4.u32 {%0,%1,%2,%3}, [%4];\n}\n"
                 : "+r"(v.x), "+r"(v.y), "+r"(v.z), "+r"(v.w) : "l"(p), "r"(live) : "memory");
}
__device__ __forceinline__ void ldg_relaxed64_p(unsigned long long& v, const unsigned long long* p, unsigned live) {
    asm volatile("{\n.reg .pred p;\nsetp.ne.u32 p, %2, 0;\n@p ld.relaxed.gpu.global.u64 %0, [%1];\n}\n" : "+l"(v) : "l"(p), "r"(live) : "memory");
}
__device__ __forceinline__ void ldg_relaxed64x2_p(ulonglong2& v, const unsigned long long* p, unsigned live) {
    asm volatile("{\n.reg .pred p;\nsetp.ne.u32 p, %3, 0;\n@p ld.relaxed.gpu.global.v2.u64 {%0,%1}, [%2];\n}\n"
                 : "+l"(v.x), "+l"(v.y) : "l"(p), "r"(live) : "memory");
}
__device__ __forceinline__ void stg_relaxed1_p(unsigned* p, unsigned v, unsigned live) {
    asm volatile("{\n.reg .pred p;\nsetp.ne.u32 p, %2, 0;\n@p st.relaxed.gpu.global.u32 [%0], %1;\n}\n" ::"l"(p), "r"(v), "r"(live) : "memory");
}
__device__ __forceinline__ void stg_relaxed2_p(unsigned* p, unsigned a, unsigned b, unsigned live) {
    asm volatile("{\n.reg .pred p;\nsetp.ne.u32 p, %3, 0;\n@p st.relaxed.gpu.global.v2.u32 [%0], {%1,%2};\n}\n" ::"l"(p), "r"(a), "r"(b), "r"(live) : "memory");
}
__device__ __forceinline__ void stg_relaxed64_p(unsigned long long* p, float v, unsigned tag, unsigned live) {
    const unsigned long long w = ((unsigned long long)__float_as_uint(v) << 32) | tag;
    asm volatile("{\n.reg .pred p;\nsetp.ne.u32 p, %2, 0;\n@p st.relaxed.gpu.global.u64 [%0], %1;\n}\n" ::"l"(p), "l"(w), "r"(live) : "memory");
}
__device__ __forceinline__ void sts32_p(uint32_t addr, unsigned v, unsigned live) {
    asm volatile("{\n.reg .pred p;\nsetp.ne.u32 p, %2, 0;\n@p st.shared.u32 [%0], %1;\n}\n" ::"r"(addr), "r"(v), "r"(live) : "memory");
}
__device__ __forceinline__ void sts16_p(uint32_t addr, unsigned v, unsigned live) {
    asm volatile("{\n.reg .pred p;\nsetp.ne.u32 p, %2, 0;\n@p st.shared.u16 [%0], %1;\n}\n" ::"r"(addr), "h"((unsigned short)v), "r"(live) : "memory");
}
__device__ __forceinline__ void sts128_p(uint32_t addr, float a, float b, float c, float d, unsigned live) {
    asm volatile("{\n.reg .pred p;\nsetp.ne.u32 p, %5, 0;\n@p st.shared.v4.f32 [%0], {%1,%2,%3,%4};\n}\n"
                 ::"r"(addr), "f"(a), "f"(b), "f"(c), "f"(d), "r"(live) : "memory");
}
__device__ __forceinline__ void stg16_p(void* p, unsigned v, unsigned live) {
    asm volatile("{\n.reg .pred p;\nsetp.ne.u32 p, %2, 0;\n@p st.global.u16 [%0], %1;\n}\n" ::"l"(p), "h"((unsigned short)v), "r"(live) : "memory");
}

__device__ __forceinline__ float bfr(float x) { return __bfloat162float(__float2bfloat16_rn(x)); }
__device__ __forceinline__ unsigned bf_bits(float x) { return (unsigned)__bfloat16_as_ushort(__float2bfloat16_rn(x)); }
__device__ __forceinline__ float bf_hi(unsigned w) { return __uint_as_float(w & 0xffff0000u); }
__device__ __forceinline__ float bf_lo(unsigned w) { return __uint_as_float(w << 16); }
__device__ __forceinline__ unsigned pack_hi(unsigned lo_word, unsigned hi_word) {
    return __byte_perm(lo_word, hi_word, 0x7632);
}
__device__ __forceinline__ unsigned pack_bf2(float lo, float hi) {
    unsigned r; asm("cvt.rn.bf16x2.f32 %0, %1, %2;" : "=r"(r) : "f"(hi), "f"(lo)); return r;
}
constexpr float LOG2E = 1.4426950408889634f;
constexpr float QSCALE = 0.08838834764831845f;
constexpr unsigned SPIN_LIMIT = 1u << 22;

template <int N>
__device__ __forceinline__ void fix_row16(const unsigned* base, int lane, unsigned tag16, uint2 (&v)[N], unsigned live = 1) {
    unsigned spins = 0;
    while (live) {
        bool ok = true;
#pragma unroll
        for (int i = 0; i < N; i++) {
            if ((v[i].x & 0xffffu) != tag16 || (v[i].y & 0xffffu) != tag16) {
                v[i] = ldg_relaxed2(base + 2 * (lane + 32 * i));
                ok = false;
            }
        }
        if (ok) break;
        if (++spins > SPIN_LIMIT) TRAP_AT(__LINE__);
    }
}
template <int N>
__device__ __forceinline__ void load_row16(const unsigned* base, int lane, uint2 (&v)[N]) {
#pragma unroll
    for (int i = 0; i < N; i++) v[i] = ldg_relaxed2(base + 2 * (lane + 32 * i));
}
template <int N>
__device__ __forceinline__ void load_row16_p(const unsigned* base, int lane, uint2 (&v)[N], unsigned live) {
#pragma unroll
    for (int i = 0; i < N; i++) { v[i] = make_uint2(0u, 0u); ldg_relaxed2_p(v[i], base + 2 * (lane + 32 * i), live); }
}

__device__ __forceinline__ void ln_stats(const float (&x)[18], float& mean_r, float& sd_r) {
    float s = 0.f;
#pragma unroll
    for (int i = 0; i < 18; i++) s += x[i];
#pragma unroll
    for (int o = 16; o; o >>= 1) s += __shfl_xor_sync(0xffffffffu, s, o);
    const float mean = s * (1.0f / 576.0f);
    float q = 0.f;
#pragma unroll
    for (int i = 0; i < 18; i++) { float d = x[i] - mean; q += d * d; }
#pragma unroll
    for (int o = 16; o; o >>= 1) q += __shfl_xor_sync(0xffffffffu, q, o);
    const float var = bfr(q * (1.0f / 576.0f));
    mean_r = bfr(mean);
    sd_r = bfr(sqrtf(bfr(var + 1e-5f)));
}
__device__ __forceinline__ float ln_mod(float x, float mean_r, float sd_r, float cmul, float sadd) {
    float y = bfr(bfr(x - mean_r) / sd_r);
    y = bfr(y * bfr(1.0f + cmul));
    return bfr(y + sadd);
}

__device__ __forceinline__ int pick_victim(const uint4 v, int lane, unsigned salt, int excl) {
    const unsigned w[4] = {v.x, v.y, v.z, v.w};
    unsigned wt[4], sum = 0;
#pragma unroll
    for (int i = 0; i < 4; i++) {
        const int rem = (UNITS - U0) - (int)(w[i] & 0xffffu);
        unsigned x = 0;
        if (rem > 0 && 4 * lane + i != excl) {
            x = (unsigned)__fdividef((float)(rem * 8), (float)((w[i] >> 16) + 1u)) + 1u;
            x = x * x;
        }
        sum += x;
        wt[i] = sum;
    }
    unsigned inc = sum;
#pragma unroll
    for (int o = 1; o < 32; o <<= 1) {
        const unsigned u = __shfl_up_sync(0xffffffffu, inc, o);
        if (lane >= o) inc += u;
    }
    const unsigned total = __shfl_sync(0xffffffffu, inc, 31);
    if (total == 0) return -1;
    unsigned h = salt * 0x9E3779B1u;
    h ^= h >> 15; h *= 0x85EBCA6Bu; h ^= h >> 13;
    const unsigned r = __umulhi(h, total);
    const int src = __ffs(__ballot_sync(0xffffffffu, inc > r)) - 1;
    const unsigned rl = r - (inc - sum);
    const int idx = (rl >= wt[0]) + (rl >= wt[1]) + (rl >= wt[2]);
    return 4 * src + __shfl_sync(0xffffffffu, idx, src);
}

__device__ __noinline__ float proj_reduce(uint32_t sb, unsigned char* sp, uint32_t base0, uint32_t base1, uint32_t base2,
                                          uint32_t pitch, int nks, int rmax, unsigned* part, unsigned tag2, int tid, unsigned live) {
    const int warp = tid >> 5, lane = tid & 31, cta = blockIdx.x;
    const int g = lane >> 2, t = lane & 3;
    if (nks == 2) TS(17);
    {
        const uint32_t bAct = sb + SM_ACT + (g * ACT_PITCH + 2 * t) * 2;
        uint32_t bf[3][2];
#pragma unroll
        for (int ks = 0; ks < 3; ks++) { bf[ks][0] = lds32(bAct + ks * 32); bf[ks][1] = lds32(bAct + ks * 32 + 16); }
        const int kr = (lane & 7) + 8 * (lane >> 4), cs = (lane >> 3) & 1;
        unsigned* dst0 = part + (size_t)cta * (DM * NB) + g * 8 + 2 * t;
#pragma unroll 1
        for (int tile = warp; tile < 36; tile += 8) {
            const int cbk = tile >> 2;
            const int j = cbk / 3;
            const uint32_t box = (j == 0 ? base0 : j == 1 ? base1 : base2) + (cbk - 3 * j) * pitch;
            const int ch = (tile & 3) * 2 + cs;
            float acc[4] = {0.f, 0.f, 0.f, 0.f};
#pragma unroll
            for (int ks = 0; ks < 3; ks++) {
                if (ks < nks) {
                    int r = 16 * ks + kr;
                    if (r > rmax) r = rmax;
                    uint32_t a[4];
                    ldsm4t(box + r * 128 + ((ch ^ (r & 7)) << 4), a);
                    mma16816(acc, a, bf[ks][0], bf[ks][1]);
                }
            }
            unsigned* dst = dst0 + 128 * tile;
            stg_relaxed2_p(dst, (__float_as_uint(acc[0]) & ~3u) | tag2, (__float_as_uint(acc[1]) & ~3u) | tag2, live);
            stg_relaxed2_p(dst + 64, (__float_as_uint(acc[2]) & ~3u) | tag2, (__float_as_uint(acc[3]) & ~3u) | tag2, live);
            if (nks == 2 && tile == warp) TS(18);
        }
    }
    TS(nks == 2 ? 7 : 11);
    float s = 0.f;
    if (cta < 72) {
        const float4* s_red = reinterpret_cast<const float4*>(sp + SM_RED);
        const int ch = lane & 15, sl = lane >> 4;
        const unsigned* ptr = part + (size_t)(16 * warp + sl) * (DM * NB) + 64 * cta + 4 * ch;
        uint4 v[8];
#pragma unroll
        for (int i = 0; i < 8; i++) { v[i] = make_uint4(0u, 0u, 0u, 0u); ldg_relaxed4_p(v[i], ptr + (size_t)(2 * i) * (DM * NB), live); }
        unsigned spins = 0;
        while (live) {
            bool ok = true;
#pragma unroll
            for (int i = 0; i < 8; i++) {
                if ((v[i].x & 3u) != tag2 || (v[i].y & 3u) != tag2 || (v[i].z & 3u) != tag2 || (v[i].w & 3u) != tag2) {
                    v[i] = ldg_relaxed4(ptr + (size_t)(2 * i) * (DM * NB));
                    ok = false;
                }
            }
            if (ok) break;
            if (++spins > SPIN_LIMIT) TRAP_AT(__LINE__);
        }
        if (nks == 2) TS(19);
        float f[4] = {0.f, 0.f, 0.f, 0.f};
#pragma unroll
        for (int i = 0; i < 8; i++) {
            f[0] += __uint_as_float(v[i].x & ~3u); f[1] += __uint_as_float(v[i].y & ~3u);
            f[2] += __uint_as_float(v[i].z & ~3u); f[3] += __uint_as_float(v[i].w & ~3u);
        }
#pragma unroll
        for (int e = 0; e < 4; e++) f[e] += __shfl_xor_sync(0xffffffffu, f[e], 16);
        sts128_p(sb + SM_RED + (warp * 16 + ch) * 16, f[0], f[1], f[2], f[3], live && lane < 16);
        cons_sync_p(live);
        if (tid < 64) {
            const float* r = reinterpret_cast<const float*>(s_red);
            const int vi = (tid & 7) * 8 + (tid >> 3);
#pragma unroll
            for (int w = 0; w < 8; w++) s += r[w * 64 + vi];
        }
    }
    return s;
}

__global__ void __launch_bounds__(NTHREADS, 1)
fused_kernel(const __grid_constant__ CUtensorMap tmK, const __grid_constant__ CUtensorMap tmV,
             const __grid_constant__ CUtensorMap tmMod, const __grid_constant__ CUtensorMap tmQ,
             const __grid_constant__ CUtensorMap tmO, const __grid_constant__ CUtensorMap tmG,
             const __grid_constant__ CUtensorMap tmU, const __grid_constant__ CUtensorMap tmD,
             const Params prm) {
    extern __shared__ unsigned char smem_raw[];
    const uint32_t sb = (smem_u32(smem_raw) + 1023u) & ~1023u;
    unsigned char* sp = smem_raw + (sb - smem_u32(smem_raw));
    const int lane = threadIdx.x & 31;
    const int rwarp = threadIdx.x >> 5;
    unsigned live;
    asm volatile("mov.u32 %0, %1;" : "=r"(live) : "r"(rwarp < 8 ? 1u : 0u));
    const int warp = live ? rwarp : 0, tid = warp * 32 + lane;
    const int cta = blockIdx.x;
    const uint32_t bar_full = sb + SM_BAR, bar_empty = sb + SM_BAR + 64, bar_ctrl = sb + SM_BAR + 128;
    const uint32_t bar_wm = sb + SM_BAR + 160, bar_wq = bar_wm + 8, bar_wo = bar_wm + 16, bar_gate = bar_wm + 24;
    volatile int2* meta = reinterpret_cast<volatile int2*>(sp + SM_META);
    volatile unsigned* s_epoch = reinterpret_cast<volatile unsigned*>(sp + SM_EPOCH);

    if (rwarp == 8) {
        if (lane == 0) {
            const unsigned e = ldg_relaxed1(&g_epoch);
            for (int i = 0; i < NTILE; i++) { mbar_init(bar_full + 8 * i, 1); mbar_init(bar_empty + 8 * i, 4); }
            for (int i = 0; i < 8; i++) mbar_init(bar_ctrl + 8 * i, 1);
            asm volatile("fence.mbarrier_init.release.cluster;" ::: "memory");
            asm volatile("fence.proxy.async.shared::cta;" ::: "memory");
            if (cta < 108) {
                mbar_expect_tx(bar_wm, 36864);
                const int cA = cta < 36 ? 16 * cta : 1152 + 32 * (cta - 36);
                const int cB = cta < 36 ? 576 + 16 * cta : cA + 16;
                for (int i = 0; i < 3; i++) {
                    tma2d(sb + SM_WREG + i * 6144, &tmMod, cA, 192 * i, bar_wm);
                    tma2d(sb + SM_WREG + 18432 + i * 6144, &tmMod, cB, 192 * i, bar_wm);
                }
            } else {
                mbar_arrive(bar_wm);
            }
            if (cta < NROLE) {
                mbar_expect_tx(bar_wq, 36864);
                for (int i = 0; i < 3; i++) tma2d(sb + SM_WB + i * 12288, &tmQ, 32 * cta, 192 * i, bar_wq);
            } else {
                mbar_arrive(bar_wq);
            }
            prefetch_map(&tmK); prefetch_map(&tmV);
            *s_epoch = e;
            atomicAdd(&g_started[e & 1], 1u);
        }
        __syncthreads();
        const unsigned epoch = *s_epoch;
        const int par = epoch & 1;
        unsigned* ctr = g_ctr[par];
        const unsigned salt = 2u * (unsigned)cta + 1u;
        int cur = (cta < NROLE) ? cta : -1;
        int vslot = 0;
        int gslot0 = 0, gslot1 = 0;
        int pend_pair = -1; bool pend_fresh = false; unsigned pend = 0;
        bool known_end = false;
        uint4 scanv = make_uint4(0, 0, 0, 0);
        bool scan_ok = false, hk_done = (cta != 0);
        int excl = -1;
        auto wchunk = [&](int i) {
            if (i < 3) {
                if (i == 0) mbar_expect_tx(bar_wo, 36864);
                for (int r = 0; r < 3; r++)
                    tma2d(sb + SM_WREG + (3 * i + r) * 4096, &tmO, 64 * (3 * i + r), 32 * cta, bar_wo);
            } else {
                if (i == 3) mbar_expect_tx(bar_gate, 46080);
                tma2d(sb + SM_WB + (i - 3) * 15360, &tmG, (36 * cta) & ~7, 192 * (i - 3), bar_gate);
            }
        };
        auto housekeeping = [&]() {
            if (lane == 0) {
                unsigned spins = 0;
                while (ldg_relaxed1(&g_started[par]) < gridDim.x) { if (++spins > SPIN_LIMIT) TRAP_AT(__LINE__); }
                g_started[par ^ 1] = 0;
                g_epoch = epoch + 1;
            }
            *reinterpret_cast<uint4*>(&g_ctr[par ^ 1][4 * lane]) = make_uint4(0, 0, 0, 0);
        };
        int n = 0;
        for (;; n++) {
            int unit = -1;
            if (cta < NROLE && n < U0) {
                unit = n;
            } else {
                if (pend_pair >= 0) {
                    const unsigned old = __shfl_sync(0xffffffffu, pend, 0);
                    const unsigned tk = (old & 0xffffu) + U0;
                    if (tk < (unsigned)UNITS) {
                        unit = (int)tk;
                        if (pend_fresh) { cur = pend_pair; vslot = (int)(old >> 16) + 1; }
                    }
                    else excl = pend_pair;
                    pend_pair = -1;
                }
                while (unit < 0 && !known_end) {
                    if (!scan_ok) scanv = ldg_relaxed4(ctr + 4 * lane);
                    scan_ok = false;
                    const int v = pick_victim(scanv, lane, salt + 2u * 977u * (unsigned)n, excl);
                    if (v < 0) break;
                    const unsigned old = __shfl_sync(0xffffffffu, atom_add_lane0(ctr + v, 0x10001u, lane), 0);
                    const unsigned tk = (old & 0xffffu) + U0;
                    if (tk < (unsigned)UNITS) { unit = (int)tk; cur = v; vslot = (int)(old >> 16) + 1; }
                    else excl = v;
                }
                if (unit < 0) break;
            }
            if (n >= U0 - 1 || cta >= NROLE) {
                if (unit < UNITS - 1) {
                    pend = atom_add_lane0(ctr + cur, 1u, lane);
                    pend_pair = cur; pend_fresh = false;
                    if (unit >= UNITS - 12) { scanv = ldg_relaxed4(ctr + 4 * lane); scan_ok = true; }
                } else if (scan_ok) {
                    const int v = pick_victim(scanv, lane, salt + 2u * 977u * (unsigned)n, cur);
                    if (v < 0) known_end = true;
                    else {
                        pend = atom_add_lane0(ctr + v, 0x10001u, lane);
                        pend_pair = v; pend_fresh = true;
                        scanv = ldg_relaxed4(ctr + 4 * lane);
                    }
                } else {
                    scanv = ldg_relaxed4(ctr + 4 * lane); scan_ok = true;
                }
            }
            const int iK = 2 * n;
            const int sK = iK & 7;
            const uint32_t eph = ((iK >> 3) & 1) ^ 1;
            mbar_wait(bar_empty + 8 * sK, eph);
            const int row = (cur * SK + unit * UKEYS) * 2;
            if (lane == 0) {
                meta[n & 3].x = cur; meta[n & 3].y = (n & 1) ? gslot1 : gslot0;
                mbar_arrive(bar_ctrl + 8 * (n & 3));
            }
            if (n & 1) gslot1 = vslot; else gslot0 = vslot;
            if (iK >= INFL) mbar_wait(bar_full + 8 * ((iK - INFL) & 7), ((iK - INFL) >> 3) & 1);
            else if (iK == 0) mbar_wait(bar_wm, 0);
            else if (iK == 2) mbar_wait(bar_wq, 0);
            if (lane == 0) {
                mbar_expect_tx(bar_full + 8 * sK, TILE);
                tma2d(sb + SM_RING + sK * TILE, &tmK, 0, row, bar_full + 8 * sK);
            }
            mbar_wait(bar_empty + 8 * (sK + 1), eph);
            if (iK + 1 >= INFL) mbar_wait(bar_full + 8 * ((iK + 1 - INFL) & 7), ((iK + 1 - INFL) >> 3) & 1);
            if (lane == 0) {
                mbar_expect_tx(bar_full + 8 * (sK + 1), TILE);
                tma2d(sb + SM_RING + (sK + 1) * TILE, &tmV, 0, row, bar_full + 8 * (sK + 1));
                if (cta < NROLE && n >= WSTART && n < WSTART + 6) wchunk(n - WSTART);
            }
            __syncwarp();
            if (!hk_done && n == 12) { housekeeping(); hk_done = true; }
        }
        TSP(13);
        if (!hk_done) housekeeping();
        if (lane == 0) {
            for (int e = 0; e < 2; e++) {
                const int ne = n + e;
                mbar_wait(bar_empty + 8 * ((2 * ne) & 7), (((2 * ne) >> 3) & 1) ^ 1);
                meta[ne & 3].x = -1 - n; meta[ne & 3].y = (ne & 1) ? gslot1 : gslot0;
                mbar_arrive(bar_ctrl + 8 * (ne & 3));
            }
            if (cta < NROLE) {
                const int gc = (36 * cta) & ~7;
                for (int i = max(0, n - WSTART); i < 6; i++) wchunk(i);
                for (int i = 0; i < 6; i++) {
                    const int it = 2 * n + i;
                    const int s = it & 7;
                    const uint32_t dst = sb + SM_RING + s * TILE;
                    const uint32_t fb = bar_full + 8 * s;
                    mbar_wait(bar_empty + 8 * s, ((it >> 3) & 1) ^ 1);
                    mbar_wait(bar_full + 8 * ((it - TINFL) & 7), ((it - TINFL) >> 3) & 1);
                    if (i < 3) {
                        mbar_expect_tx(fb, 15360);
                        tma2d(dst, &tmU, gc, 192 * i, fb);
                    } else {
                        mbar_expect_tx(fb, 3 * 4608);
                        for (int r = 0; r < 3; r++) tma2d(dst + r * 5120, &tmD, 64 * (3 * (i - 3) + r), 36 * cta, fb);
                    }
                }
            }
        }
        TSG(26, 256);
        return;
    }

    const int g = lane >> 2, t = lane & 3;
    TS(0);
    TSG(24, 288);
    const uint32_t bufA = sb + SM_BUFA;
    float* s_stat = reinterpret_cast<float*>(sp + SM_STAT);
    if (live && cta < 108) {
        const unsigned* cw = reinterpret_cast<const unsigned*>(prm.c) + warp * 288;
        unsigned cv[9];
#pragma unroll
        for (int i = 0; i < 9; i++) cv[i] = __ldg(cw + lane + 32 * i);
        if (cta < 36) {
            const unsigned* xw = reinterpret_cast<const unsigned*>(prm.x) + warp * 288;
            float xv[18];
#pragma unroll
            for (int i = 0; i < 9; i++) { unsigned w = __ldg(xw + lane + 32 * i); xv[2 * i] = bf_lo(w); xv[2 * i + 1] = bf_hi(w); }
            float mr, sr;
            ln_stats(xv, mr, sr);
            if (lane == 0) { s_stat[2 * warp] = mr; s_stat[2 * warp + 1] = sr; }
        }
#pragma unroll
        for (int i = 0; i < 9; i++) {
            float a = bf_lo(cv[i]), b = bf_hi(cv[i]);
            a = a / (1.0f + expf(-a));
            b = b / (1.0f + expf(-b));
            *reinterpret_cast<unsigned*>(sp + SM_BUFA + (warp * BUFA_PITCH + 2 * (lane + 32 * i)) * 2) = pack_bf2(a, b);
        }
    }
    __syncthreads();
    const unsigned epoch = *s_epoch;
    const int par = epoch & 1;
    const unsigned tag16 = epoch % 65535u + 1u;
    const unsigned tag2 = epoch % 3u + 1u;
    const unsigned tagR = (epoch % 0xffffffu + 1u) << 8;
    float4* s_red = reinterpret_cast<float4*>(sp + SM_RED);
    const uint32_t bA = bufA + (g * BUFA_PITCH + 2 * t) * 2;

    if (live && cta < 108) {
        mbar_wait(bar_wm, 0);
        const int tile = warp & 1, kq = warp >> 1;
        float acc[4] = {0.f, 0.f, 0.f, 0.f};
        const int kr = (lane & 7) + 8 * (lane >> 4);
        const uint32_t boxb = sb + SM_WREG + ((lane >> 3) & 1) * 18432;
#pragma unroll
        for (int i = 0; i < 9; i++) {
            const int ks = kq * 9 + i;
            const int r = 16 * ks + kr;
            uint32_t a[4];
            ldsm4t(boxb + r * 32 + ((tile ^ ((r >> 2) & 1)) << 4), a);
            const uint32_t b0 = lds32(bA + ks * 32), b1 = lds32(bA + ks * 32 + 16);
            mma16816(acc, a, b0, b1);
        }
        s_red[warp * 32 + lane] = make_float4(acc[0], acc[1], acc[2], acc[3]);
        cons_sync();
        if (warp < 2) {
            float4 v = s_red[warp * 32 + lane];
#pragma unroll
            for (int k = 1; k < 4; k++) { float4 u = s_red[(warp + 2 * k) * 32 + lane]; v.x += u.x; v.y += u.y; v.z += u.z; v.w += u.w; }
            const int cl = 8 * warp + g;
            if (cta < 36) {
                const int col = 16 * cta + cl;
#pragma unroll
                for (int e = 0; e < 2; e++) {
                    const int b = 2 * t + e;
                    const float sa = bfr(e ? v.y : v.x), ca = bfr(e ? v.w : v.z);
                    const float xv = __bfloat162float(prm.x[b * DM + col]);
                    const float h = ln_mod(xv, s_stat[2 * b], s_stat[2 * b + 1], ca, sa);
                    stg_relaxed1(&g_h[b * DM + col], (bf_bits(h) << 16) | tag16);
                }
            } else {
                const int colA = 1152 + 32 * (cta - 36) + cl, colB = colA + 16;
                stg_relaxed1(&g_mod[(2 * t) * 3456 + colA], (bf_bits(v.x) << 16) | tag16);
                stg_relaxed1(&g_mod[(2 * t + 1) * 3456 + colA], (bf_bits(v.y) << 16) | tag16);
                stg_relaxed1(&g_mod[(2 * t) * 3456 + colB], (bf_bits(v.z) << 16) | tag16);
                stg_relaxed1(&g_mod[(2 * t + 1) * 3456 + colB], (bf_bits(v.w) << 16) | tag16);
            }
        }
    }
    TS(1);
    if (live && cta < NROLE) {
        uint2 hv[9];
        load_row16<9>(g_h + warp * DM, lane, hv);
        fix_row16<9>(g_h + warp * DM, lane, tag16, hv);
        cons_sync();
#pragma unroll
        for (int i = 0; i < 9; i++)
            *reinterpret_cast<unsigned*>(sp + SM_BUFA + (warp * BUFA_PITCH + 2 * (lane + 32 * i)) * 2) = pack_hi(hv[i].x, hv[i].y);
        cons_sync();
        mbar_wait(bar_wq, 0);
        const int tile = warp & 1, kq = warp >> 1;
        float acc[4] = {0.f, 0.f, 0.f, 0.f};
        const int kr = (lane & 7) + 8 * (lane >> 4);
        const int ch = 2 * tile + ((lane >> 3) & 1);
#pragma unroll
        for (int i = 0; i < 9; i++) {
            const int ks = kq * 9 + i;
            const int r = 16 * ks + kr;
            uint32_t a[4];
            ldsm4t(sb + SM_WB + r * 64 + ((ch ^ ((r >> 1) & 3)) << 4), a);
            const uint32_t b0 = lds32(bA + ks * 32), b1 = lds32(bA + ks * 32 + 16);
            mma16816(acc, a, b0, b1);
        }
        s_red[warp * 32 + lane] = make_float4(acc[0], acc[1], acc[2], acc[3]);
        cons_sync();
        if (warp < 2) {
            float4 v = s_red[warp * 32 + lane];
#pragma unroll
            for (int k = 1; k < 4; k++) { float4 u = s_red[(warp + 2 * k) * 32 + lane]; v.x += u.x; v.y += u.y; v.z += u.z; v.w += u.w; }
            const int col = 32 * cta + 16 * warp + g;
            stg_relaxed1(&g_q[(2 * t) * 4096 + col], (bf_bits(v.x) << 16) | tag16);
            stg_relaxed1(&g_q[(2 * t + 1) * 4096 + col], (bf_bits(v.y) << 16) | tag16);
            stg_relaxed1(&g_q[(2 * t) * 4096 + col + 8], (bf_bits(v.z) << 16) | tag16);
            stg_relaxed1(&g_q[(2 * t + 1) * 4096 + col + 8], (bf_bits(v.w) << 16) | tag16);
        }
    }
    TS(2);
    unsigned cpk[9], spk[9];
    const int ob = (tid >> 3) & 7, ocol = 8 * cta + (tid & 7);
    const bool oth = cta < 72 && tid < 64;
    unsigned gab = 0; float xin = 0.f;
#pragma unroll
    for (int i = 0; i < 9; i++) { cpk[i] = 0; spk[i] = 0; }
    if (!live) {
        if (cta >= NROLE) return;
        mbar_wait(bar_gate, 0);
    }
    int dpass = 0;
dry_again:
    if (live && cta < NROLE) {
        uint2 cbv[9], sbv[9];
        load_row16<9>(g_mod + warp * 3456 + 4 * DM, lane, cbv);
        load_row16<9>(g_mod + warp * 3456 + 3 * DM, lane, sbv);
        if (oth) {
            unsigned gaw, gbw, spins = 0;
            xin = __bfloat162float(prm.x[ob * DM + ocol]);
            do {
                gaw = ldg_relaxed1(&g_mod[ob * 3456 + 2 * DM + ocol]);
                gbw = ldg_relaxed1(&g_mod[ob * 3456 + 5 * DM + ocol]);
                if (++spins > SPIN_LIMIT) TRAP_AT(__LINE__);
            } while ((gaw & 0xffffu) != tag16 || (gbw & 0xffffu) != tag16);
            gab = pack_hi(gaw, gbw);
        }
        fix_row16<9>(g_mod + warp * 3456 + 4 * DM, lane, tag16, cbv);
        fix_row16<9>(g_mod + warp * 3456 + 3 * DM, lane, tag16, sbv);
#pragma unroll
        for (int i = 0; i < 9; i++) {
            cpk[i] = pack_bf2(1.0f + bf_hi(cbv[i].x), 1.0f + bf_hi(cbv[i].y));
            spk[i] = pack_hi(sbv[i].x, sbv[i].y);
        }
    }

    const int grp = warp >> 2, wq = warp & 3;
    int n = grp;
    int nend = 0;
    unsigned cw0 = 0;
    {
        uint32_t kpre[2], vpre[2];
        {
            const int key = (lane & 7) + 8 * ((lane >> 3) & 1), cs = lane >> 4;
#pragma unroll
            for (int h = 0; h < 2; h++) {
                const int r = 2 * (16 * wq + key) + h;
                kpre[h] = r * 128 + ((cs ^ (r & 7)) << 4);
            }
            const int kr = (lane & 7), hi = lane >> 4, cv = (lane >> 3) & 1;
            const int vkey = (kr >> 1) + 8 * (kr & 1) + 4 * hi;
#pragma unroll
            for (int h = 0; h < 2; h++) {
                const int r = 2 * (16 * wq + vkey) + h;
                vpre[h] = r * 128 + ((cv ^ (r & 7)) << 4);
            }
        }
        uint32_t qf[8][2];
        float o[8][4];
        float m = -INFINITY, l = 0.f;
        int cur = live ? -1 : 0, cnt = 0;
#pragma unroll
        for (int i = 0; i < 8; i++) { qf[i][0] = qf[i][1] = 0; o[i][0] = o[i][1] = o[i][2] = o[i][3] = 0.f; }
        const volatile float* scr_o = reinterpret_cast<const volatile float*>(sp + SM_BUFA + grp * 4096);
        const volatile float* scr_ml = reinterpret_cast<const volatile float*>(sp + SM_ML + grp * 64);
        for (;; n += 2) {
            const uint32_t ph = (n >> 2) & 1;
            int np = -1, fslot = 0;
            if (live) {
                mbar_wait(bar_ctrl + 8 * (n & 3), ph);
                np = meta[n & 3].x; fslot = meta[n & 3].y;
            }
            if (np != cur) {
                uint2 qa[8], qb2[8];
                const unsigned* qb = g_q + ((np < 0 ? 0 : np) >> 4) * 4096 + ((np < 0 ? 0 : np) & 15) * 256 + (g & 1) * 128 + 2 * t;
                if (np >= 0) {
#pragma unroll
                    for (int ks = 0; ks < 8; ks++) { qa[ks] = ldg_relaxed2(qb + 16 * ks); qb2[ks] = ldg_relaxed2(qb + 16 * ks + 8); }
                } else {
                    ldg_relaxed1_p(cw0, &g_ctr[par][warp * HKV + ((cta >> 3) & 15)], live);
                }
                if (cur >= 0) {
#pragma unroll
                    for (int of = 4; of <= 16; of <<= 1) l += __shfl_xor_sync(0xffffffffu, l, of);
                    {
                        const unsigned wr = live && t == 0;
                        const uint32_t so = sb + SM_BUFA + grp * 4096 + (wq * 256 + g) * 4;
#pragma unroll
                        for (int mt = 0; mt < 8; mt++) {
                            sts32_p(so + mt * 64, __float_as_uint(o[mt][0]), wr);
                            sts32_p(so + 512 + mt * 64, __float_as_uint(o[mt][1]), wr);
                            sts32_p(so + mt * 64 + 32, __float_as_uint(o[mt][2]), wr);
                            sts32_p(so + 512 + mt * 64 + 32, __float_as_uint(o[mt][3]), wr);
                        }
                        const uint32_t sm = sb + SM_ML + grp * 64 + (wq * 2 + lane) * 8;
                        sts32_p(sm, __float_as_uint(m), live && lane < 2);
                        sts32_p(sm + 4, __float_as_uint(l), live && lane < 2);
                    }
                    group_sync_p(grp, live);
                    {
                        const int d = tid & 127;
                        unsigned long long* rec = g_part + ((size_t)(2 * fslot + grp) * NPAIR + cur) * RSTRIDE;
#pragma unroll
                        for (int h = 0; h < 2; h++) {
                            float M = -INFINITY;
#pragma unroll
                            for (int w = 0; w < 4; w++) M = fmaxf(M, scr_ml[(w * 2 + h) * 2]);
                            float O = 0.f, L = 0.f;
#pragma unroll
                            for (int w = 0; w < 4; w++) {
                                const float f = ex2((scr_ml[(w * 2 + h) * 2] - M) * LOG2E);
                                O += f * scr_o[(w * 2 + h) * 128 + d];
                                L += f * scr_ml[(w * 2 + h) * 2 + 1];
                            }
                            stg_relaxed64_p(rec + h * 128 + d, O, tagR, live);
                            stg_relaxed64_p(rec + 256 + 2 * h, M, tagR, live && d == h);
                            stg_relaxed64_p(rec + 257 + 2 * h, L, tagR | (unsigned)cnt, live && d == h);
                        }
                    }
                    group_sync_p(grp, live);
                }
                if (np < 0) { nend = -1 - np; break; }
                cur = np; cnt = 0;
                m = -INFINITY; l = 0.f;
#pragma unroll
                for (int mt = 0; mt < 8; mt++) { o[mt][0] = o[mt][1] = o[mt][2] = o[mt][3] = 0.f; }
                unsigned spins = 0;
                while (true) {
                    bool ok = true;
#pragma unroll
                    for (int ks = 0; ks < 8; ks++) {
                        ok = ok && ((qa[ks].x & 0xffffu) == tag16) && ((qa[ks].y & 0xffffu) == tag16) &&
                             ((qb2[ks].x & 0xffffu) == tag16) && ((qb2[ks].y & 0xffffu) == tag16);
                    }
                    if (__all_sync(0xffffffffu, ok)) break;
                    if (++spins > SPIN_LIMIT) TRAP_AT(__LINE__);
                    __nanosleep(64);
#pragma unroll
                    for (int ks = 0; ks < 8; ks++) { qa[ks] = ldg_relaxed2(qb + 16 * ks); qb2[ks] = ldg_relaxed2(qb + 16 * ks + 8); }
                }
#pragma unroll
                for (int ks = 0; ks < 8; ks++) { qf[ks][0] = pack_hi(qa[ks].x, qa[ks].y); qf[ks][1] = pack_hi(qb2[ks].x, qb2[ks].y); }
            }
            if (n == 0) TS(3);
            if (n == 4) TS(4);
            const int sK = (2 * n) & 7;
            const uint32_t kb = sb + SM_RING + sK * TILE, vb = kb + TILE;
            mbar_wait(bar_full + 8 * sK, ph);
            float c0[4] = {0.f, 0.f, 0.f, 0.f}, c1[4] = {0.f, 0.f, 0.f, 0.f};
#pragma unroll
            for (int ks = 0; ks < 8; ks += 2) {
                uint32_t a[4], b[4];
                ldsm4(kb + (kpre[ks >> 2] ^ ((ks & 3) << 5)), a);
                ldsm4(kb + (kpre[(ks + 1) >> 2] ^ (((ks + 1) & 3) << 5)), b);
                mma16816(c0, a, qf[ks][0], qf[ks][1]);
                mma16816(c1, b, qf[ks + 1][0], qf[ks + 1][1]);
            }
            __syncwarp();
            if (lane == 0) mbar_arrive(bar_empty + 8 * sK);
            float s0 = (t & 1) ? (c0[1] + c1[1]) : (c0[0] + c1[0]);
            float s1 = (t & 1) ? (c0[3] + c1[3]) : (c0[2] + c1[2]);
            s0 = bfr(bfr(s0) * QSCALE);
            s1 = bfr(bfr(s1) * QSCALE);
            float bm = fmaxf(s0, s1);
            if (__any_sync(0xffffffffu, bm > m)) {
#pragma unroll
                for (int of = 4; of <= 16; of <<= 1) bm = fmaxf(bm, __shfl_xor_sync(0xffffffffu, bm, of));
                const float mn = fmaxf(m, bm);
                const float al = ex2((m - mn) * LOG2E);
                m = mn; l *= al;
                const float alo = __shfl_xor_sync(0xffffffffu, al, 1);
                const float a0 = (t & 1) ? alo : al, a1 = (t & 1) ? al : alo;
#pragma unroll
                for (int mt = 0; mt < 8; mt++) { o[mt][0] *= a0; o[mt][1] *= a1; o[mt][2] *= a0; o[mt][3] *= a1; }
            }
            const float p0 = ex2((s0 - m) * LOG2E), p1 = ex2((s1 - m) * LOG2E);
            l += p0 + p1;
            const unsigned pk = pack_bf2(p0, p1);
            const unsigned pb0 = __shfl_sync(0xffffffffu, pk, 4 * t + (g & 1));
            const unsigned pb1 = __shfl_sync(0xffffffffu, pk, 4 * (t + 4) + (g & 1));
            mbar_wait(bar_full + 8 * (sK + 1), ph);
#pragma unroll
            for (int mt = 0; mt < 8; mt++) {
                uint32_t a[4];
                ldsm4t(vb + (vpre[mt >> 2] ^ ((mt & 3) << 5)), a);
                mma16816(o[mt], a, pb0, pb1);
            }
            __syncwarp();
            if (lane == 0) mbar_arrive(bar_empty + 8 * (sK + 1));
            cnt++;
        }
    }
    TS(5);
    TS2(15);
    if (threadIdx.x == 0) TSV(16, 2 * nend + 2);
    if (cta >= NROLE) return;

    {
        const int p = warp * HKV + (cta >> 3);
        const int head = (cta >> 2) & 1;
        const unsigned long long* rec = g_part + (size_t)p * RSTRIDE;
        constexpr size_t RS = (size_t)NPAIR * RSTRIDE;
        const int ooff = (cta & 7) * 32 + lane, hoff = 256 + 2 * head;
        unsigned long long ow[16];
        ulonglong2 hd = make_ulonglong2(0ull, 0ull);
        unsigned got = 0;
        bool hv = false;
        const int lim = live ? 2 * (int)((cw0 >> 16) + 1u) : 0;
        unsigned spins = 0;
        unsigned vmask, tot32;
#pragma unroll
        for (int r = 0; r < 16; r++) ow[r] = 0ull;
        while (true) {
            ldg_relaxed64x2_p(hd, rec + lane * RS + hoff, !hv && lane < lim);
#pragma unroll
            for (int r = 0; r < 16; r++)
                ldg_relaxed64_p(ow[r], rec + r * RS + ooff, r < lim && !((got >> r) & 1u));
            hv = hv || (lane < lim && (unsigned)hd.x == tagR && ((unsigned)hd.y & ~0xffu) == tagR);
#pragma unroll
            for (int r = 0; r < 16; r++)
                if (r < lim && (unsigned)ow[r] == tagR) got |= 1u << r;
            vmask = __ballot_sync(0xffffffffu, hv);
            tot32 = __reduce_add_sync(0xffffffffu, hv ? ((unsigned)hd.y & 0xffu) : 0u);
            unsigned tot = tot32;
            if (tot32 != (unsigned)UNITS && lim > 32) {
                unsigned extra = 0;
                for (int r = 32 + lane; r < lim; r += 32) {
                    const ulonglong2 h2 = ldg_relaxed64x2(rec + r * RS + hoff);
                    if ((unsigned)h2.x == tagR && ((unsigned)h2.y & ~0xffu) == tagR) extra += (unsigned)h2.y & 0xffu;
                }
                tot += __reduce_add_sync(0xffffffffu, extra);
            }
            const unsigned need = vmask & 0xffffu;
            if (!live || (tot == (unsigned)UNITS && __all_sync(0xffffffffu, (got & need) == need))) break;
            if (++spins > SPIN_LIMIT) TRAP_AT(__LINE__);
        }
        if (threadIdx.x == 0) { TSV(14, lim); TSV(22, spins); }
        TS(21);
        float Mr = hv ? __uint_as_float((unsigned)(hd.x >> 32)) : -INFINITY;
        float Lr = hv ? __uint_as_float((unsigned)(hd.y >> 32)) : 0.f;
        float M = lane < 16 ? Mr : -INFINITY;
#pragma unroll
        for (int of = 16; of; of >>= 1) M = fmaxf(M, __shfl_xor_sync(0xffffffffu, M, of));
        const float f = (lane < 16 && hv) ? ex2((Mr - M) * LOG2E) : 0.f;
        float L = f * Lr;
#pragma unroll
        for (int of = 16; of; of >>= 1) L += __shfl_xor_sync(0xffffffffu, L, of);
        float acc = 0.f;
#pragma unroll
        for (int r = 0; r < 16; r++) {
            const float fr = __shfl_sync(0xffffffffu, f, r);
            if ((vmask >> r) & 1u) acc += fr * __uint_as_float((unsigned)(ow[r] >> 32));
        }
        if (live && ((vmask >> 16) != 0u || tot32 != (unsigned)UNITS)) {
            const int lim2 = tot32 != (unsigned)UNITS ? lim : 32;
            for (int base = 0; base < lim2; base += 32) {
                bool v2 = hv;
                if (base) {
                    v2 = false;
                    if (base + lane < lim) {
                        hd = ldg_relaxed64x2(rec + (base + lane) * RS + hoff);
                        v2 = (unsigned)hd.x == tagR && ((unsigned)hd.y & ~0xffu) == tagR;
                    }
                    Mr = __uint_as_float((unsigned)(hd.x >> 32)); Lr = __uint_as_float((unsigned)(hd.y >> 32));
                }
                unsigned mk = __ballot_sync(0xffffffffu, v2);
                if (base == 0) mk &= 0xffff0000u;
                while (mk) {
                    const int r = __ffs(mk) - 1;
                    mk &= mk - 1;
                    const float Mx = __shfl_sync(0xffffffffu, Mr, r), Lx = __shfl_sync(0xffffffffu, Lr, r);
                    unsigned long long w;
                    unsigned sp2 = 0;
                    while ((unsigned)(w = ldg_relaxed64(rec + (base + r) * RS + ooff)) != tagR) { if (++sp2 > SPIN_LIMIT) TRAP_AT(__LINE__); }
                    const float Mn = fmaxf(M, Mx);
                    const float fo = ex2((M - Mn) * LOG2E), fn = ex2((Mx - Mn) * LOG2E);
                    M = Mn; L = L * fo + Lx * fn;
                    acc = acc * fo + __uint_as_float((unsigned)(w >> 32)) * fn;
                }
            }
        }
        sts16_p(sb + SM_ACT + (warp * ACT_PITCH + lane) * 2, bf_bits(__fdividef(acc, L)), live);
        sts32_p(sb + SM_ACT + (warp * ACT_PITCH + 32 + 2 * lane) * 2, 0u, live && lane < 8);
    }
    if (live) mbar_wait(bar_wo, 0);
    cons_sync_p(live);
    TS(6);
    {
        const float s = proj_reduce(sb, sp, sb + SM_WREG, sb + SM_WREG + 12288, sb + SM_WREG + 24576, 4096, 2, 31, g_wop, tag2, tid, live);
        if (oth) {
            xin = bfr(xin + bfr(bf_lo(gab) * bfr(s)));
            stg_relaxed1_p(&g_x2[ob * DM + ocol], (bf_bits(xin) << 16) | tag16, live);
        }
    }
    TS(8);
    {
        uint2 xv2[9];
        load_row16_p<9>(g_x2 + warp * DM, lane, xv2, live);
        fix_row16<9>(g_x2 + warp * DM, lane, tag16, xv2, live);
        TS(20);
        float xf[18];
#pragma unroll
        for (int i = 0; i < 9; i++) { xf[2 * i] = bf_hi(xv2[i].x); xf[2 * i + 1] = bf_hi(xv2[i].y); }
        float mr, sr;
        ln_stats(xf, mr, sr);
#pragma unroll
        for (int i = 0; i < 9; i++) {
            const float h0 = bfr(bfr(__fdividef(bfr(xf[2 * i] - mr), sr)) * bf_lo(cpk[i])) + bf_lo(spk[i]);
            const float h1 = bfr(bfr(__fdividef(bfr(xf[2 * i + 1] - mr), sr)) * bf_hi(cpk[i])) + bf_hi(spk[i]);
            sts32_p(sb + SM_BUFA + (warp * BUFA_PITCH + 2 * (lane + 32 * i)) * 2, pack_bf2(h0, h1), live);
        }
    }
    cons_sync_p(live);
    TS(9);
    uint32_t sl[6];
#pragma unroll
    for (int i = 0; i < 6; i++) sl[i] = sb + SM_RING + ((2 * nend + i) & 7) * TILE;
    if (warp < 5) {
        if (live) {
            mbar_wait(bar_gate, 0);
#pragma unroll
            for (int i = 0; i < 3; i++) mbar_wait(bar_full + 8 * ((2 * nend + i) & 7), ((2 * nend + i) >> 3) & 1);
        }
        const bool isup = (lane >> 3) & 1;
        const int kr = (lane & 7) + 8 * (lane >> 4);
        uint32_t base[3];
#pragma unroll
        for (int i = 0; i < 3; i++) base[i] = isup ? sl[i] : sb + SM_WB + i * 15360;
        float acc[4][4];
#pragma unroll
        for (int i = 0; i < 4; i++) acc[i][0] = acc[i][1] = acc[i][2] = acc[i][3] = 0.f;
#pragma unroll
        for (int ks = 0; ks < 36; ks++) {
            const int r = (16 * ks) % 192 + kr;
            uint32_t a[4];
            ldsm4t(base[ks / 12] + r * 80 + warp * 16, a);
            mma16816(acc[ks & 3], a, lds32(bA + ks * 32), lds32(bA + ks * 32 + 16));
        }
        const int cl = 8 * warp + g - 4 * (cta & 1);
#pragma unroll
        for (int e = 0; e < 2; e++) {
            const float gt = bfr(acc[0][e] + acc[1][e] + acc[2][e] + acc[3][e]);
            const float up = bfr(acc[0][2 + e] + acc[1][2 + e] + acc[2][2 + e] + acc[3][2 + e]);
            const float inner = 0.7978845608028654f * (gt + 0.044715f * gt * gt * gt);
            const float ge = bfr(0.5f * gt * (1.0f + tanhf(inner)));
            sts16_p(sb + SM_ACT + ((2 * t + e) * ACT_PITCH + cl) * 2, bf_bits(ge * up), live && cl >= 0 && cl < 36);
        }
    } else if (tid >= 160 && tid < 208) {
        const int i = tid - 160;
        *reinterpret_cast<unsigned*>(sp + SM_ACT + ((i / 6) * ACT_PITCH + 36 + 2 * (i % 6)) * 2) = 0;
    }
    if (live) {
#pragma unroll
        for (int i = 3; i < 6; i++) mbar_wait(bar_full + 8 * ((2 * nend + i) & 7), ((2 * nend + i) >> 3) & 1);
    }
    cons_sync_p(live);
    TS(10);
    {
        const float s = proj_reduce(sb, sp, sl[3], sl[4], sl[5], 5120, 3, 35, g_dnp, tag2, tid, live);
        if (oth) {
            stg16_p(prm.out + ob * DM + ocol, bf_bits(xin + bfr(bf_hi(gab) * bfr(s))), live);
        }
    }
    TS(12);
#define NDRY 1
    if (!live) {
        dpass++;
        if (dpass < NDRY) goto dry_again;
    }
}

typedef CUresult (*EncodeFn)(CUtensorMap*, CUtensorMapDataType, cuuint32_t, void*, const cuuint64_t*, const cuuint64_t*,
                             const cuuint32_t*, const cuuint32_t*, CUtensorMapInterleave, CUtensorMapSwizzle,
                             CUtensorMapL2promotion, CUtensorMapFloatOOBfill);

bool make_map(EncodeFn fn, CUtensorMap* m, const void* ptr, uint64_t inner, uint64_t outer, uint64_t stride_bytes,
              uint32_t box_inner, uint32_t box_outer, CUtensorMapSwizzle sw, CUtensorMapL2promotion promo) {
    cuuint64_t dims[2] = {inner, outer};
    cuuint64_t strides[1] = {stride_bytes};
    cuuint32_t box[2] = {box_inner, box_outer};
    cuuint32_t es[2] = {1, 1};
    return fn(m, CU_TENSOR_MAP_DATA_TYPE_BFLOAT16, 2, const_cast<void*>(ptr), dims, strides, box, es,
              CU_TENSOR_MAP_INTERLEAVE_NONE, sw, promo, CU_TENSOR_MAP_FLOAT_OOB_FILL_NONE) == CUDA_SUCCESS;
}

}

extern "C" void kernel_launch(void* const* d_in, const int* in_sizes, int n_in, void* d_out, int out_size) {
    (void)in_sizes; (void)n_in; (void)out_size;
    static EncodeFn encode = nullptr;
    static int num_sms = 0;
    if (!encode) {
        void* fn = nullptr;
        cudaDriverEntryPointQueryResult qres;
        cudaGetDriverEntryPoint("cuTensorMapEncodeTiled", &fn, cudaEnableDefault, &qres);
        encode = (EncodeFn)fn;
        int dev = 0;
        cudaGetDevice(&dev);
        cudaDeviceGetAttribute(&num_sms, cudaDevAttrMultiProcessorCount, dev);
        cudaFuncSetAttribute(fused_kernel, cudaFuncAttributeMaxDynamicSharedMemorySize, SMEM_BYTES);
    }
    CUtensorMap tmK, tmV, tmMod, tmQ, tmO, tmG, tmU, tmD;
    const uint64_t kvrows = (uint64_t)NB * HKV * SK * 2;
    make_map(encode, &tmK, d_in[1], 64, kvrows, 128, 64, 128, CU_TENSOR_MAP_SWIZZLE_128B, CU_TENSOR_MAP_L2_PROMOTION_L2_256B);
    make_map(encode, &tmV, d_in[2], 64, kvrows, 128, 64, 128, CU_TENSOR_MAP_SWIZZLE_128B, CU_TENSOR_MAP_L2_PROMOTION_L2_256B);
    make_map(encode, &tmQ, d_in[3], 4096, DM, 8192, 32, 192, CU_TENSOR_MAP_SWIZZLE_64B, CU_TENSOR_MAP_L2_PROMOTION_L2_128B);
    make_map(encode, &tmO, d_in[4], DM, 4096, DM * 2, 64, 32, CU_TENSOR_MAP_SWIZZLE_128B, CU_TENSOR_MAP_L2_PROMOTION_L2_128B);
    make_map(encode, &tmG, d_in[6], FF, DM, FF * 2, 40, 192, CU_TENSOR_MAP_SWIZZLE_NONE, CU_TENSOR_MAP_L2_PROMOTION_L2_128B);
    make_map(encode, &tmU, d_in[7], FF, DM, FF * 2, 40, 192, CU_TENSOR_MAP_SWIZZLE_NONE, CU_TENSOR_MAP_L2_PROMOTION_L2_128B);
    make_map(encode, &tmD, d_in[8], DM, FF, DM * 2, 64, 36, CU_TENSOR_MAP_SWIZZLE_128B, CU_TENSOR_MAP_L2_PROMOTION_L2_128B);
    make_map(encode, &tmMod, d_in[10], 6 * DM, DM, 6 * DM * 2, 16, 192, CU_TENSOR_MAP_SWIZZLE_32B, CU_TENSOR_MAP_L2_PROMOTION_L2_128B);
    Params prm;
    prm.x = (const __nv_bfloat16*)d_in[0];
    prm.c = (const __nv_bfloat16*)d_in[9];
    prm.out = (__nv_bfloat16*)d_out;
    int grid = num_sms < MAXCTA ? num_sms : MAXCTA;
    fused_kernel<<<grid, NTHREADS, SMEM_BYTES>>>(tmK, tmV, tmMod, tmQ, tmO, tmG, tmU, tmD, prm);
}
```

```cpp
#include <cuda_runtime.h>
#include <cuda_bf16.h>
#include <cuda.h>
#include <stdint.h>

namespace {

constexpr int NB = 8;
constexpr int DM = 576;
constexpr int SK = 8192;
constexpr int FF = 4608;
constexpr int NPAIR = 128;
constexpr int UKEYS = 64;
constexpr int UNITS = SK / UKEYS;
constexpr int U0 = 4;
constexpr int TILE = 16384;
constexpr int NTILE = 8;
#define INFL 4
#define INFL0 INFL
#define NRAMP 8
#define TINFL 2
#define WSTART 6
#define NCLR 48
#define NMOD 16
#define KVGATE 2
#define WEARLY 0
#define WQD 1
#define NCD 1200
constexpr int NROLE = 128;
constexpr int NRED = 72;
constexpr int MAXCTA = 132;
constexpr int MAXREC = 2 * (MAXCTA + 1);
constexpr int RSTRIDE = 272;
constexpr int NTHREADS = 288;

constexpr int SM_RING = 0;
constexpr int SM_WREG = NTILE * TILE;
constexpr int SM_WB = SM_WREG + 36864;
constexpr int SM_BUFA = SM_WREG + 82944;
constexpr int BUFA_PITCH = 584;
constexpr int SM_RED = SM_BUFA + 8 * BUFA_PITCH * 2;
constexpr int SM_ACT = SM_RED + 4096;
constexpr int ACT_PITCH = 56;
constexpr int SM_ML = SM_ACT + 8 * ACT_PITCH * 2;
constexpr int SM_STAT = SM_ML + 128;
constexpr int SM_META = SM_STAT + 64;
constexpr int SM_BAR = SM_META + 32;
constexpr int SM_EPOCH = SM_BAR + 28 * 8;
constexpr int SM_TOTAL = SM_EPOCH + 16;
constexpr int SMEM_BYTES = SM_TOTAL + 1024;

__device__ __align__(16) unsigned g_ctr[2][NPAIR];
__device__ unsigned g_epoch;
__device__ unsigned g_started[2];
__device__ __align__(16) unsigned g_h[NB * DM];
__device__ __align__(16) unsigned g_mod[NB * 6 * DM];
__device__ __align__(16) unsigned g_q[NB * 4096];
__device__ __align__(128) unsigned long long g_part[(size_t)MAXREC * NPAIR * RSTRIDE];
__device__ __align__(128) unsigned g_wop[(size_t)NROLE * DM * NB];
__device__ __align__(128) unsigned g_x2[NB * DM / 2];
__device__ __align__(128) unsigned g_dnp[(size_t)NROLE * DM * NB];

struct Params {
    const __nv_bfloat16* x;
    const __nv_bfloat16* c;
    const __nv_bfloat16* wmod;
    __nv_bfloat16* out;
};

#define TRAP_AT(line) __trap()
#define TS(i)
#define TSL(i)
#define TS2(i)
#define TSP(i)
#define TSG(i, thr)
#define TSV(i, v)
#define TW(i)

__device__ __forceinline__ uint32_t smem_u32(const void* p) { return (uint32_t)__cvta_generic_to_shared(p); }
__device__ __forceinline__ void mbar_init(uint32_t bar, uint32_t cnt) {
    asm volatile("mbarrier.init.shared::cta.b64 [%0], %1;" ::"r"(bar), "r"(cnt) : "memory");
}
__device__ __forceinline__ void mbar_expect_tx(uint32_t bar, uint32_t bytes) {
    asm volatile("mbarrier.arrive.expect_tx.shared::cta.b64 _, [%0], %1;" ::"r"(bar), "r"(bytes) : "memory");
}
__device__ __forceinline__ void mbar_arrive(uint32_t bar) {
    asm volatile("mbarrier.arrive.shared::cta.b64 _, [%0];" ::"r"(bar) : "memory");
}
__device__ __forceinline__ bool mbar_try(uint32_t bar, uint32_t parity) {
    uint32_t ok;
    asm volatile(
        "{\n.reg .pred p;\n"
        "mbarrier.try_wait.parity.shared::cta.b64 p, [%1], %2;\n"
        "selp.u32 %0, 1, 0, p;\n}\n"
        : "=r"(ok) : "r"(bar), "r"(parity) : "memory");
    return ok != 0;
}
__device__ __forceinline__ bool mbar_test(uint32_t bar, uint32_t parity) {
    uint32_t ok;
    asm volatile(
        "{\n.reg .pred p;\n"
        "mbarrier.test_wait.parity.shared::cta.b64 p, [%1], %2;\n"
        "selp.u32 %0, 1, 0, p;\n}\n"
        : "=r"(ok) : "r"(bar), "r"(parity) : "memory");
    return ok != 0;
}
__device__ __noinline__ void mbar_wait_slow(uint32_t bar, uint32_t parity) {
    unsigned long long t0, t1;
    asm volatile("mov.u64 %0, %globaltimer;" : "=l"(t0));
    while (!mbar_try(bar, parity)) {
        asm volatile("mov.u64 %0, %globaltimer;" : "=l"(t1));
        if (t1 - t0 > 2000000000ull) TRAP_AT(__LINE__);
    }
}
__device__ __forceinline__ void mbar_wait(uint32_t bar, uint32_t parity) {
    if (!mbar_try(bar, parity)) mbar_wait_slow(bar, parity);
}
__device__ __forceinline__ void tma2d(uint32_t dst, const CUtensorMap* map, int c0, int c1, uint32_t bar) {
    asm volatile(
        "cp.async.bulk.tensor.2d.shared::cluster.global.mbarrier::complete_tx::bytes [%0], [%1, {%3, %4}], [%2];"
        ::"r"(dst), "l"((uint64_t)map), "r"(bar), "r"(c0), "r"(c1) : "memory");
}
__device__ __forceinline__ void tma2d_s(uint32_t dst, const CUtensorMap* map, int c0, int c1, uint32_t bar, uint64_t pol) {
    asm volatile(
        "cp.async.bulk.tensor.2d.shared::cluster.global.mbarrier::complete_tx::bytes.L2::cache_hint [%0], [%1, {%3, %4}], [%2], %5;"
        ::"r"(dst), "l"((uint64_t)map), "r"(bar), "r"(c0), "r"(c1), "l"(pol) : "memory");
}
__device__ __forceinline__ void prefetch_map(const CUtensorMap* map) {
    asm volatile("prefetch.tensormap [%0];" ::"l"((uint64_t)map) : "memory");
}
__device__ __forceinline__ void cp_async16(uint32_t dst, const void* src) {
    asm volatile("cp.async.cg.shared.global [%0], [%1], 16;" ::"r"(dst), "l"(src) : "memory");
}
__device__ __forceinline__ void ldsm4(uint32_t addr, uint32_t (&r)[4]) {
    asm volatile("ldmatrix.sync.aligned.m8n8.x4.shared.b16 {%0,%1,%2,%3}, [%4];"
                 : "=r"(r[0]), "=r"(r[1]), "=r"(r[2]), "=r"(r[3]) : "r"(addr) : "memory");
}
__device__ __forceinline__ void ldsm2(uint32_t addr, uint32_t& r0, uint32_t& r1) {
    asm volatile("ldmatrix.sync.aligned.m8n8.x2.shared.b16 {%0,%1}, [%2];" : "=r"(r0), "=r"(r1) : "r"(addr) : "memory");
}
__device__ __forceinline__ void ldsm4t(uint32_t addr, uint32_t (&r)[4]) {
    asm volatile("ldmatrix.sync.aligned.m8n8.x4.trans.shared.b16 {%0,%1,%2,%3}, [%4];"
                 : "=r"(r[0]), "=r"(r[1]), "=r"(r[2]), "=r"(r[3]) : "r"(addr) : "memory");
}
__device__ __forceinline__ void mma16816(float (&c)[4], const uint32_t (&a)[4], uint32_t b0, uint32_t b1) {
    asm volatile(
        "mma.sync.aligned.m16n8k16.row.col.f32.bf16.bf16.f32 {%0,%1,%2,%3}, {%4,%5,%6,%7}, {%8,%9}, {%0,%1,%2,%3};"
        : "+f"(c[0]), "+f"(c[1]), "+f"(c[2]), "+f"(c[3])
        : "r"(a[0]), "r"(a[1]), "r"(a[2]), "r"(a[3]), "r"(b0), "r"(b1));
}
__device__ __forceinline__ void cons_sync() { asm volatile("bar.sync 1, 256;" ::: "memory"); }
__device__ __forceinline__ void group_sync(int grp) { asm volatile("bar.sync %0, 128;" ::"r"(2 + grp) : "memory"); }
__device__ __forceinline__ uint32_t lds32(uint32_t addr) {
    uint32_t v; asm volatile("ld.shared.u32 %0, [%1];" : "=r"(v) : "r"(addr) : "memory"); return v;
}
__device__ __forceinline__ float2 lds64f(uint32_t addr) {
    float2 v; asm volatile("ld.shared.v2.f32 {%0,%1}, [%2];" : "=f"(v.x), "=f"(v.y) : "r"(addr) : "memory"); return v;
}
__device__ __forceinline__ float4 lds128f(uint32_t addr) {
    float4 v; asm volatile("ld.shared.v4.f32 {%0,%1,%2,%3}, [%4];" : "=f"(v.x), "=f"(v.y), "=f"(v.z), "=f"(v.w) : "r"(addr) : "memory"); return v;
}
__device__ __forceinline__ void sts32(uint32_t addr, unsigned v) {
    asm volatile("st.shared.u32 [%0], %1;" ::"r"(addr), "r"(v) : "memory");
}
__device__ __forceinline__ void sts16(uint32_t addr, unsigned v) {
    asm volatile("st.shared.u16 [%0], %1;" ::"r"(addr), "h"((unsigned short)v) : "memory");
}
__device__ __forceinline__ void sts64f(uint32_t addr, float a, float b) {
    asm volatile("st.shared.v2.f32 [%0], {%1,%2};" ::"r"(addr), "f"(a), "f"(b) : "memory");
}
__device__ __forceinline__ void sts128f(uint32_t addr, float a, float b, float c, float d) {
    asm volatile("st.shared.v4.f32 [%0], {%1,%2,%3,%4};" ::"r"(addr), "f"(a), "f"(b), "f"(c), "f"(d) : "memory");
}
__device__ __forceinline__ uint2 ldg_relaxed2(const unsigned* p) {
    uint2 v; asm volatile("ld.relaxed.gpu.global.v2.u32 {%0,%1}, [%2];" : "=r"(v.x), "=r"(v.y) : "l"(p) : "memory"); return v;
}
__device__ __forceinline__ uint4 ldg_relaxed4(const unsigned* p) {
    uint4 v; asm volatile("ld.relaxed.gpu.global.v4.u32 {%0,%1,%2,%3}, [%4];"
                          : "=r"(v.x), "=r"(v.y), "=r"(v.z), "=r"(v.w) : "l"(p) : "memory"); return v;
}
__device__ __forceinline__ unsigned ldg_relaxed1(const unsigned* p) {
    unsigned v; asm volatile("ld.relaxed.gpu.global.u32 %0, [%1];" : "=r"(v) : "l"(p) : "memory"); return v;
}
__device__ __forceinline__ unsigned ldg_acquire1(const unsigned* p) {
    unsigned v; asm volatile("ld.acquire.gpu.global.u32 %0, [%1];" : "=r"(v) : "l"(p) : "memory"); return v;
}
__device__ __forceinline__ ulonglong2 ldg_relaxed64x2(const unsigned long long* p) {
    ulonglong2 v; asm volatile("ld.relaxed.gpu.global.v2.u64 {%0,%1}, [%2];" : "=l"(v.x), "=l"(v.y) : "l"(p) : "memory"); return v;
}
__device__ __forceinline__ void ldg_relaxed64x2_p(ulonglong2& v, const unsigned long long* p, bool pr) {
    asm volatile("{\n.reg .pred p;\nsetp.ne.u32 p, %3, 0;\n@p ld.relaxed.gpu.global.v2.u64 {%0,%1}, [%2];\n}\n"
                 : "+l"(v.x), "+l"(v.y) : "l"(p), "r"((unsigned)pr) : "memory");
}
__device__ __forceinline__ void stg_relaxed1(unsigned* p, unsigned v) {
    asm volatile("st.relaxed.gpu.global.u32 [%0], %1;" ::"l"(p), "r"(v) : "memory");
}
__device__ __forceinline__ void stg_relaxed4(unsigned* p, unsigned a, unsigned b, unsigned c, unsigned d) {
    asm volatile("st.relaxed.gpu.global.v4.u32 [%0], {%1,%2,%3,%4};" ::"l"(p), "r"(a), "r"(b), "r"(c), "r"(d) : "memory");
}
__device__ __forceinline__ unsigned long long tagged(float v, unsigned tag) {
    return ((unsigned long long)__float_as_uint(v) << 32) | tag;
}
__device__ __forceinline__ void stg_relaxed64x2(unsigned long long* p, unsigned long long a, unsigned long long b) {
    asm volatile("st.relaxed.gpu.global.v2.u64 [%0], {%1,%2};" ::"l"(p), "l"(a), "l"(b) : "memory");
}
__device__ __forceinline__ unsigned atom_add_lane0(unsigned* p, unsigned inc, int lane) {
    unsigned v = 0;
    asm volatile("{\n.reg .pred p;\nsetp.eq.s32 p, %3, 0;\n@p atom.relaxed.gpu.global.add.u32 %0, [%1], %2;\n}\n"
                 : "+r"(v) : "l"(p), "r"(inc), "r"(lane) : "memory");
    return v;
}
__device__ __forceinline__ float ex2(float x) { float y; asm("ex2.approx.ftz.f32 %0, %1;" : "=f"(y) : "f"(x)); return y; }
__device__ __forceinline__ float rcp(float x) { float y; asm("rcp.approx.ftz.f32 %0, %1;" : "=f"(y) : "f"(x)); return y; }

__device__ __forceinline__ float bfr(float x) { return __bfloat162float(__float2bfloat16_rn(x)); }
__device__ __forceinline__ unsigned bf_bits(float x) { return (unsigned)__bfloat16_as_ushort(__float2bfloat16_rn(x)); }
__device__ __forceinline__ float bf_hi(unsigned w) { return __uint_as_float(w & 0xffff0000u); }
__device__ __forceinline__ float bf_lo(unsigned w) { return __uint_as_float(w << 16); }
__device__ __forceinline__ unsigned pack_hi(unsigned lo_word, unsigned hi_word) {
    return __byte_perm(lo_word, hi_word, 0x7632);
}
__device__ __forceinline__ unsigned pack_bf2(float lo, float hi) {
    unsigned r; asm("cvt.rn.bf16x2.f32 %0, %1, %2;" : "=r"(r) : "f"(hi), "f"(lo)); return r;
}
__device__ __forceinline__ unsigned bf2_sub(unsigned a, unsigned b) { unsigned r; asm("sub.rn.bf16x2 %0, %1, %2;" : "=r"(r) : "r"(a), "r"(b)); return r; }
__device__ __forceinline__ unsigned bf2_mul(unsigned a, unsigned b) { unsigned r; asm("mul.rn.bf16x2 %0, %1, %2;" : "=r"(r) : "r"(a), "r"(b)); return r; }
__device__ __forceinline__ unsigned bf2_add(unsigned a, unsigned b) { unsigned r; asm("add.rn.bf16x2 %0, %1, %2;" : "=r"(r) : "r"(a), "r"(b)); return r; }
constexpr float LOG2E = 1.4426950408889634f;
constexpr float QSCALE = 0.08838834764831845f;
constexpr unsigned SPIN_LIMIT = 1u << 22;

template <int N>
__device__ __forceinline__ void fix_row16(const unsigned* base, int lane, unsigned tag16, uint2 (&v)[N]) {
    unsigned spins = 0;
    while (true) {
        bool ok = true;
#pragma unroll
        for (int i = 0; i < N; i++) {
            if ((v[i].x & 0xffffu) != tag16 || (v[i].y & 0xffffu) != tag16) {
                v[i] = ldg_relaxed2(base + 2 * (lane + 32 * i));
                ok = false;
            }
        }
        if (ok) break;
        if (++spins > SPIN_LIMIT) TRAP_AT(__LINE__);
    }
}
template <int N>
__device__ __forceinline__ void load_row16(const unsigned* base, int lane, uint2 (&v)[N]) {
#pragma unroll
    for (int i = 0; i < N; i++) v[i] = ldg_relaxed2(base + 2 * (lane + 32 * i));
}

__device__ __forceinline__ void ln_stats(const unsigned (&w)[9], unsigned& mean2, float& rsd) {
    const float sh = __shfl_sync(0xffffffffu, bf_lo(w[0]), 0);
    float s = 0.f, q = 0.f;
#pragma unroll
    for (int i = 0; i < 9; i++) {
        const float a = bf_lo(w[i]) - sh, b = bf_hi(w[i]) - sh;
        s += a + b;
        q = fmaf(a, a, q); q = fmaf(b, b, q);
    }
#pragma unroll
    for (int o = 16; o; o >>= 1) { s += __shfl_xor_sync(0xffffffffu, s, o); q += __shfl_xor_sync(0xffffffffu, q, o); }
    const float md = s * (1.0f / 576.0f);
    const float var = bfr(fmaxf(fmaf(-md, md, q * (1.0f / 576.0f)), 0.f));
    mean2 = pack_bf2(md + sh, md + sh);
    rsd = rcp(bfr(sqrtf(bfr(var + 1e-5f))));
}
__device__ __forceinline__ unsigned ln_apply(unsigned w, unsigned mean2, float rsd, unsigned c1, unsigned s) {
    const unsigned d = bf2_sub(w, mean2);
    const unsigned y = pack_bf2(bf_lo(d) * rsd, bf_hi(d) * rsd);
    return bf2_add(bf2_mul(y, c1), s);
}

__device__ __forceinline__ int pick_victim(const uint4 v, int lane, unsigned salt, int excl) {
    const unsigned w[4] = {v.x, v.y, v.z, v.w};
    unsigned wt[4], sum = 0;
#pragma unroll
    for (int i = 0; i < 4; i++) {
        const int rem = (UNITS - U0) - (int)(w[i] & 0xffffu);
        unsigned x = 0;
        if (rem > 0 && 4 * lane + i != excl) {
            x = (unsigned)__fdividef((float)(rem * 8), (float)((w[i] >> 16) + 1u)) + 1u;
            x = x * x;
        }
        sum += x;
        wt[i] = sum;
    }
    unsigned inc = sum;
#pragma unroll
    for (int o = 1; o < 32; o <<= 1) {
        const unsigned u = __shfl_up_sync(0xffffffffu, inc, o);
        if (lane >= o) inc += u;
    }
    const unsigned total = __shfl_sync(0xffffffffu, inc, 31);
    if (total == 0) return -1;
    unsigned h = salt * 0x9E3779B1u;
    h ^= h >> 15; h *= 0x85EBCA6Bu; h ^= h >> 13;
    const unsigned r = __umulhi(h, total);
    const int src = __ffs(__ballot_sync(0xffffffffu, inc > r)) - 1;
    const unsigned rl = r - (inc - sum);
    const int idx = (rl >= wt[0]) + (rl >= wt[1]) + (rl >= wt[2]);
    return 4 * src + __shfl_sync(0xffffffffu, idx, src);
}

__device__ __forceinline__ const unsigned* red_ptr(const unsigned* part, int cta, int warp, int lane) {
    return part + (size_t)(16 * warp + (lane >> 4)) * (DM * NB) + 64 * cta + 4 * (lane & 15);
}
__device__ __forceinline__ void red_issue(const unsigned* ptr, uint4 (&v)[8]) {
#pragma unroll
    for (int i = 0; i < 8; i++) v[i] = ldg_relaxed4(ptr + (size_t)(2 * i) * (DM * NB));
}
__device__ __forceinline__ float red_finish(const unsigned* ptr, uint4 (&v)[8], unsigned tag2, uint32_t sb, int tid, int twi) {
    const int warp = tid >> 5, lane = tid & 31;
    unsigned spins = 0;
    while (true) {
        bool ok = true;
#pragma unroll
        for (int i = 0; i < 8; i++) {
            if ((((v[i].x ^ tag2) | (v[i].y ^ tag2) | (v[i].z ^ tag2) | (v[i].w ^ tag2)) & 3u) != 0u) {
                v[i] = ldg_relaxed4(ptr + (size_t)(2 * i) * (DM * NB));
                ok = false;
            }
        }
        if (ok) break;
        if (++spins > SPIN_LIMIT) TRAP_AT(__LINE__);
    }
    __syncwarp();
    TW(twi);
    float f[4] = {0.f, 0.f, 0.f, 0.f};
#pragma unroll
    for (int i = 0; i < 8; i++) {
        f[0] += __uint_as_float(v[i].x); f[1] += __uint_as_float(v[i].y);
        f[2] += __uint_as_float(v[i].z); f[3] += __uint_as_float(v[i].w);
    }
#pragma unroll
    for (int e = 0; e < 4; e++) f[e] += __shfl_xor_sync(0xffffffffu, f[e], 16);
    if (lane < 16) sts128f(sb + SM_RED + (warp * 16 + lane) * 16, f[0], f[1], f[2], f[3]);
    cons_sync();
    float s = 0.f;
    if (tid < 64) {
        float r[8];
#pragma unroll
        for (int w = 0; w < 8; w++) r[w] = __uint_as_float(lds32(sb + SM_RED + (w * 64 + tid) * 4));
        s = ((r[0] + r[1]) + (r[2] + r[3])) + ((r[4] + r[5]) + (r[6] + r[7]));
    }
    return s;
}
__device__ __forceinline__ void put_partial(unsigned* dst, const float (&acc)[4], unsigned tag2) {
    stg_relaxed4(dst, (__float_as_uint(acc[0]) & ~3u) | tag2, (__float_as_uint(acc[1]) & ~3u) | tag2,
                 (__float_as_uint(acc[2]) & ~3u) | tag2, (__float_as_uint(acc[3]) & ~3u) | tag2);
}

__device__ __noinline__ float combine_slow(const unsigned long long* rec, const unsigned* ctr, int d0, unsigned tagR, int lane) {
    constexpr size_t RS = (size_t)NPAIR * RSTRIDE;
    const int half = lane >> 4;
    float M = -INFINITY, L = 0.f, a0 = 0.f, a1 = 0.f;
    unsigned done[(MAXREC + 15) / 16];
    for (int i = 0; i < (MAXREC + 15) / 16; i++) done[i] = 0u;
    int tot = 0;
    unsigned spins = 0;
    while (tot != UNITS) {
        const int lim = min(2 * (int)((ldg_relaxed1(ctr) >> 16) + 1u), MAXREC);
        for (int base = 0; base < lim; base += 16) {
            ulonglong2 hd = make_ulonglong2(0ull, 0ull), w[8];
            if (base + (lane >> 1) < lim) hd = ldg_relaxed64x2(rec + (base + (lane >> 1)) * RS + 256 + 2 * (lane & 1));
#pragma unroll
            for (int i = 0; i < 8; i++) {
                w[i] = make_ulonglong2(0ull, 0ull);
                if (base + 2 * i + half < lim) w[i] = ldg_relaxed64x2(rec + (base + 2 * i + half) * RS + 2 * (d0 + (lane & 15)));
            }
            const unsigned vm = __ballot_sync(0xffffffffu, (unsigned)hd.x == tagR && ((unsigned)hd.y & ~0xffu) == tagR);
            unsigned pm = vm & (vm >> 1) & 0x55555555u & ~done[base >> 4];
#pragma unroll
            for (int i = 0; i < 8; i++) {
                const unsigned b = __ballot_sync(0xffffffffu, (unsigned)w[i].x == tagR && (unsigned)w[i].y == tagR);
                if ((b & 0xffffu) != 0xffffu) pm &= ~(1u << (4 * i));
                if ((b >> 16) != 0xffffu) pm &= ~(1u << (4 * i + 2));
            }
            if (!pm) continue;
            done[base >> 4] |= pm;
            const bool sv = (pm >> (lane & ~1)) & 1u;
            const float Mr = sv ? __uint_as_float((unsigned)(hd.x >> 32)) : -INFINITY;
            float Mn = fmaxf(M, Mr);
#pragma unroll
            for (int of = 2; of <= 16; of <<= 1) Mn = fmaxf(Mn, __shfl_xor_sync(0xffffffffu, Mn, of));
            const float fo = ex2((M - Mn) * LOG2E), f = sv ? ex2((Mr - Mn) * LOG2E) : 0.f;
            float Ls = sv ? f * __uint_as_float((unsigned)(hd.y >> 32)) : 0.f;
#pragma unroll
            for (int of = 2; of <= 16; of <<= 1) Ls += __shfl_xor_sync(0xffffffffu, Ls, of);
            L = L * fo + Ls; M = Mn;
            tot += (int)__reduce_add_sync(0xffffffffu, (sv && !(lane & 1)) ? ((unsigned)hd.y & 0xffu) : 0u);
            a0 *= __shfl_sync(0xffffffffu, fo, 0); a1 *= __shfl_sync(0xffffffffu, fo, 1);
#pragma unroll
            for (int i = 0; i < 8; i++) {
                const float f0 = __shfl_sync(0xffffffffu, f, 4 * i + 2 * half), f1 = __shfl_sync(0xffffffffu, f, 4 * i + 2 * half + 1);
                if (f0 != 0.f) a0 = fmaf(f0, __uint_as_float((unsigned)(w[i].x >> 32)), a0);
                if (f1 != 0.f) a1 = fmaf(f1, __uint_as_float((unsigned)(w[i].y >> 32)), a1);
            }
        }
        if (++spins > SPIN_LIMIT) TRAP_AT(__LINE__);
    }
    const float v = (half ? a1 : a0) + __shfl_xor_sync(0xffffffffu, half ? a0 : a1, 16);
    return __fdividef(v, __shfl_sync(0xffffffffu, L, half));
}

__global__ void __launch_bounds__(NTHREADS, 1)
fused_kernel(const __grid_constant__ CUtensorMap tmK, const __grid_constant__ CUtensorMap tmV,
             const __grid_constant__ CUtensorMap tmQ,
             const __grid_constant__ CUtensorMap tmO, const __grid_constant__ CUtensorMap tmG,
             const __grid_constant__ CUtensorMap tmU, const __grid_constant__ CUtensorMap tmD,
             const Params prm) {
    extern __shared__ unsigned char smem_raw[];
    const uint32_t sb = (smem_u32(smem_raw) + 1023u) & ~1023u;
    unsigned char* sp = smem_raw + (sb - smem_u32(smem_raw));
    const int tid = threadIdx.x, lane = tid & 31, warp = tid >> 5;
    const int cta = blockIdx.x;
    const uint32_t bar_full = sb + SM_BAR, bar_empty = sb + SM_BAR + 64, bar_ctrl = sb + SM_BAR + 128;
    const uint32_t bar_wq = sb + SM_BAR + 160, bar_wo = bar_wq + 8, bar_gate = bar_wq + 32;
    volatile int2* meta = reinterpret_cast<volatile int2*>(sp + SM_META);
    volatile unsigned* s_epoch = reinterpret_cast<volatile unsigned*>(sp + SM_EPOCH);

    if (warp == 8) {
        if (lane == 0) {
            const unsigned e = ldg_relaxed1(&g_epoch);
            for (int i = 0; i < NTILE; i++) { mbar_init(bar_full + 8 * i, 1); mbar_init(bar_empty + 8 * i, 4); }
            for (int i = 0; i < 11; i++) mbar_init(bar_ctrl + 8 * i, 1);
            asm volatile("fence.mbarrier_init.release.cluster;" ::: "memory");
            asm volatile("fence.proxy.async.shared::cta;" ::: "memory");
            prefetch_map(&tmQ); prefetch_map(&tmK); prefetch_map(&tmV);
            if (WQD == 2) { const long long t0 = clock64(); while (clock64() - t0 < NCD) { } }
            if (WQD != 1) {
                if (cta < NROLE) {
                    mbar_expect_tx(bar_wq, 36864);
                    for (int i = 0; i < 3; i++) tma2d(sb + SM_WB + i * 12288, &tmQ, 32 * cta, 192 * i, bar_wq);
                } else {
                    mbar_arrive(bar_wq);
                }
            }
            *s_epoch = e;
        }
        TSG(24, 256);
        __syncthreads();
        if (WQD == 1 && lane == 0) {
            if (cta < NROLE) {
                mbar_expect_tx(bar_wq, 36864);
                for (int i = 0; i < 3; i++) tma2d(sb + SM_WB + i * 12288, &tmQ, 32 * cta, 192 * i, bar_wq);
            } else {
                mbar_arrive(bar_wq);
            }
        }
        const unsigned epoch = *s_epoch;
        const int par = epoch & 1;
        unsigned* ctr = g_ctr[par];
        const unsigned salt = 2u * (unsigned)cta + 1u;
        uint64_t pol;
        asm volatile("createpolicy.fractional.L2::evict_first.b64 %0, 1.0;" : "=l"(pol));
        int cur = (cta < NROLE) ? cta : -1;
        int vslot = 0;
        int gslot0 = 0, gslot1 = 0;
        int pend_pair = -1; bool pend_fresh = false; unsigned pend = 0;
        bool known_end = false, fresh = false;
        unsigned slot_r = 0;
        uint4 scanv = make_uint4(0, 0, 0, 0);
        bool scan_ok = false;
        int stage = 0;
        int excl = -1;
        auto wchunk = [&](int i) {
            if (i < 3) {
                mbar_expect_tx(bar_wo + 8 * i, 12288);
                const int r0 = (cta >> 3) * 256 + (cta & 7) * 16;
                for (int r = 0; r < 6; r++) {
                    const int b = 6 * i + r;
                    const int rg = b >= 9, cb = b - 9 * rg;
                    tma2d(sb + SM_WREG + b * 2048, &tmO, 64 * cb, r0 + 128 * rg, bar_wo + 8 * i);
                }
            } else {
                mbar_expect_tx(bar_gate + 8 * (i - 3), 15360);
                tma2d(sb + SM_WB + (i - 3) * 15360, &tmG, (36 * cta) & ~7, 192 * (i - 3), bar_gate + 8 * (i - 3));
            }
        };
        auto clear_rec = [&](int pair, int slot) {
            for (int h = 0; h < 2; h++) {
                unsigned* r = reinterpret_cast<unsigned*>(g_part + ((size_t)(2 * slot + h) * NPAIR + pair) * RSTRIDE);
                for (int i = lane; i < 130; i += 32) stg_relaxed4(r + 4 * i, 0u, 0u, 0u, 0u);
            }
            __syncwarp();
        };
        auto advance = [&]() {
            if (stage == 0) {
                if (cta < NROLE) {
                    unsigned* a = g_wop + (size_t)cta * (DM * NB);
                    unsigned* b = g_dnp + (size_t)cta * (DM * NB);
                    for (int i = lane; i < DM * NB / 4; i += 32) { stg_relaxed4(a + 4 * i, 0u, 0u, 0u, 0u); stg_relaxed4(b + 4 * i, 0u, 0u, 0u, 0u); }
                    if (cta < NRED) {
                        const int wcol = 8 * (cta >> 1) + 2 * (cta & 1) + 4 * ((lane >> 1) & 1) + (lane & 1);
                        stg_relaxed1(&g_x2[(lane >> 2) * (DM / 2) + wcol], 0u);
                    }
                }
                __syncwarp();
            } else if (stage == 1) {
                if (lane == 0) {
                    asm volatile("fence.acq_rel.gpu;" ::: "memory");
                    atomicAdd(&g_started[par], 1u);
                }
            } else if (stage == 2) {
                if (lane == 0) {
                    unsigned spins = 0;
                    while (ldg_acquire1(&g_started[par]) < gridDim.x) { if (++spins > SPIN_LIMIT) TRAP_AT(__LINE__); __nanosleep(100); }
                    if (cta == 0) {
                        g_started[par ^ 1] = 0;
                        g_epoch = epoch + 1;
                    }
                }
                __syncwarp();
                if (cta == 0) *reinterpret_cast<uint4*>(&g_ctr[par ^ 1][4 * lane]) = make_uint4(0, 0, 0, 0);
            }
            stage++;
        };
        if (cta < NROLE) clear_rec(cta, 0);
        int n = 0;
        for (;; n++) {
            int unit = -1;
            if (cta < NROLE && n < U0) {
                unit = n;
            } else {
                if (pend_pair >= 0) {
                    const unsigned tk = (__shfl_sync(0xffffffffu, pend, 0) & 0xffffu) + U0;
                    if (tk < (unsigned)UNITS) {
                        unit = (int)tk;
                        if (pend_fresh) { cur = pend_pair; fresh = true; slot_r = atom_add_lane0(ctr + cur, 0x10000u, lane); }
                    }
                    else excl = pend_pair;
                    pend_pair = -1;
                }
                while (unit < 0 && !known_end) {
                    if (!scan_ok) scanv = ldg_relaxed4(ctr + 4 * lane);
                    scan_ok = false;
                    const int v = pick_victim(scanv, lane, salt + 2u * 977u * (unsigned)n, excl);
                    if (v < 0) break;
                    const unsigned tk = (__shfl_sync(0xffffffffu, atom_add_lane0(ctr + v, 1u, lane), 0) & 0xffffu) + U0;
                    if (tk < (unsigned)UNITS) { unit = (int)tk; cur = v; fresh = true; slot_r = atom_add_lane0(ctr + v, 0x10000u, lane); }
                    else excl = v;
                }
                if (unit < 0) break;
            }
            if (n >= U0 - 1 || cta >= NROLE) {
                if (unit < UNITS - 1) {
                    pend = atom_add_lane0(ctr + cur, 1u, lane);
                    pend_pair = cur; pend_fresh = false;
                    if (unit >= UNITS - 12) { scanv = ldg_relaxed4(ctr + 4 * lane); scan_ok = true; }
                } else if (scan_ok) {
                    const int v = pick_victim(scanv, lane, salt + 2u * 977u * (unsigned)n, cur);
                    if (v < 0) known_end = true;
                    else {
                        pend = atom_add_lane0(ctr + v, 1u, lane);
                        pend_pair = v; pend_fresh = true;
                        scanv = ldg_relaxed4(ctr + 4 * lane);
                    }
                } else {
                    scanv = ldg_relaxed4(ctr + 4 * lane); scan_ok = true;
                }
            }
            const int iK = 2 * n;
            const int sK = iK & 7;
            const uint32_t eph = ((iK >> 3) & 1) ^ 1;
            mbar_wait(bar_empty + 8 * sK, eph);
            const int row = (cur * SK + unit * UKEYS) * 2;
            if (lane == 0) {
                meta[n & 3].x = cur; meta[n & 3].y = (n & 1) ? gslot1 : gslot0;
                mbar_arrive(bar_ctrl + 8 * (n & 3));
            }
            const int infl = (iK < NRAMP) ? INFL0 : INFL;
            if (KVGATE == 2 && iK == 0) mbar_wait(bar_wq, 0);
            if (KVGATE == 1 && iK == 2) mbar_wait(bar_wq, 0);
            if (iK >= infl) mbar_wait(bar_full + 8 * ((iK - infl) & 7), ((iK - infl) >> 3) & 1);
            if (lane == 0) {
                mbar_expect_tx(bar_full + 8 * sK, TILE);
                tma2d_s(sb + SM_RING + sK * TILE, &tmK, 0, row, bar_full + 8 * sK, pol);
            }
            mbar_wait(bar_empty + 8 * (sK + 1), eph);
            if (iK + 1 >= infl) mbar_wait(bar_full + 8 * ((iK + 1 - infl) & 7), ((iK + 1 - infl) >> 3) & 1);
            if (lane == 0) {
                mbar_expect_tx(bar_full + 8 * (sK + 1), TILE);
                tma2d_s(sb + SM_RING + (sK + 1) * TILE, &tmV, 0, row, bar_full + 8 * (sK + 1), pol);
                if (cta < NROLE && n >= WSTART && n < WSTART + WEARLY) wchunk(n - WSTART);
            }
            __syncwarp();
            if (fresh) { vslot = (int)(__shfl_sync(0xffffffffu, slot_r, 0) >> 16) + 1; clear_rec(cur, vslot); fresh = false; }
            if (n & 1) gslot1 = vslot; else gslot0 = vslot;
            if ((stage == 0 && n >= NCLR) || (stage == 1 && n >= NCLR + 4) || (stage == 2 && n >= NCLR + 24)) advance();
        }
        TSP(13);
        while (stage < 3) advance();
        if (lane == 0) {
            for (int e = 0; e < 2; e++) {
                const int ne = n + e;
                mbar_wait(bar_empty + 8 * ((2 * ne) & 7), (((2 * ne) >> 3) & 1) ^ 1);
                meta[ne & 3].x = -1 - n; meta[ne & 3].y = (ne & 1) ? gslot1 : gslot0;
                mbar_arrive(bar_ctrl + 8 * (ne & 3));
            }
            if (cta < NROLE) {
                const int gc = (36 * cta) & ~7;
                const int early = min(max(0, n - WSTART), WEARLY);
                uint32_t hb[TINFL], hp[TINFL];
#pragma unroll
                for (int i = 0; i < TINFL; i++) {
                    const int it = 2 * n - TINFL + i;
                    hb[i] = bar_full + 8 * (it & 7); hp[i] = (it >> 3) & 1;
                }
#pragma unroll 1
                for (int i = 0; i < 12; i++) {
                    int kind, j;
                    if (i < 3) { kind = 0; j = i; }
                    else if (i < 9) { kind = (i - 3) & 1; j = kind ? ((i - 3) >> 1) : 3 + ((i - 3) >> 1); }
                    else { kind = 1; j = i - 6; }
                    if (kind == 0 && j < early) continue;
                    mbar_wait(hb[0], hp[0]);
#pragma unroll
                    for (int k = 0; k + 1 < TINFL; k++) { hb[k] = hb[k + 1]; hp[k] = hp[k + 1]; }
                    if (kind == 0) {
                        wchunk(j);
                        hb[TINFL - 1] = (j < 3) ? bar_wo + 8 * j : bar_gate + 8 * (j - 3); hp[TINFL - 1] = 0;
                    } else {
                        const int it = 2 * n + j;
                        const int s = it & 7;
                        const uint32_t dst = sb + SM_RING + s * TILE;
                        const uint32_t fb = bar_full + 8 * s;
                        mbar_wait(bar_empty + 8 * s, ((it >> 3) & 1) ^ 1);
                        if (j < 3) {
                            mbar_expect_tx(fb, 15360);
                            tma2d(dst, &tmU, gc, 192 * j, fb);
                        } else {
                            mbar_expect_tx(fb, 3 * 4608);
                            for (int r = 0; r < 3; r++) tma2d(dst + r * 5120, &tmD, 64 * (3 * (j - 3) + r), 36 * cta, fb);
                        }
                        hb[TINFL - 1] = fb; hp[TINFL - 1] = (it >> 3) & 1;
                    }
                }
            }
        }
        TSG(26, 256);
        return;
    }

    const int g = lane >> 2, t = lane & 3;
    TS(0);
    TW(0);
    const uint32_t bufA = sb + SM_BUFA;
    const uint32_t bA = bufA + (g * BUFA_PITCH + 2 * t) * 2;
    const int kr = (lane & 7) + 8 * (lane >> 4), cs = (lane >> 3) & 1;
    constexpr int SM_RED2 = SM_WREG + 73728;
    const bool crit = cta < NRED;
    const int c00 = crit ? 8 * cta : 1152 + 32 * (cta - NRED);
    const int c01 = crit ? DM + 8 * cta : c00 + 8;
    const int c1 = crit ? (cta < 32 ? 1152 + 16 * (112 + cta) : -1) : c00 + 16;
    float x0 = 0.f, x1 = 0.f;
    if (cta < NROLE) {
        const unsigned* cw = reinterpret_cast<const unsigned*>(prm.c) + warp * 288;
        unsigned cv[9], xw[9];
#pragma unroll
        for (int i = 0; i < 9; i++) cv[i] = __ldg(cw + lane + 32 * i);
        if (crit) {
#pragma unroll
            for (int i = 0; i < 9; i++) xw[i] = __ldg(reinterpret_cast<const unsigned*>(prm.x) + warp * 288 + lane + 32 * i);
            if (warp == 0) {
                x0 = __bfloat162float(prm.x[(2 * t) * DM + 8 * cta + g]);
                x1 = __bfloat162float(prm.x[(2 * t + 1) * DM + 8 * cta + g]);
            }
#pragma unroll
            for (int i = 0; i < 5; i++) {
                const int q = tid + 256 * i;
                const int r = q >> 1, ch = q & 1;
                if (q < 1152) cp_async16(sb + SM_WREG + r * 32 + ((ch ^ ((r >> 2) & 1)) << 4), prm.wmod + (size_t)r * 3456 + (ch ? c01 : c00));
            }
        }
        asm volatile("cp.async.commit_group;" ::: "memory");
        if (warp == 1) {
#pragma unroll
            for (int i = 0; i < 2; i++) stg_relaxed4(&g_q[(4 * i + g / 2) * 4096 + 32 * cta + 4 * (lane & 7)], 0u, 0u, 0u, 0u);
        } else if (warp == 2) {
            if (crit && lane < 16) stg_relaxed4(&g_h[(lane >> 1) * DM + 8 * cta + 4 * (lane & 1)], 0u, 0u, 0u, 0u);
            for (int i = lane; i < 48; i += 32) sts32(sb + SM_ACT + ((i / 6) * ACT_PITCH + 36 + 2 * (i % 6)) * 2, 0u);
        }
#pragma unroll
        for (int i = 0; i < 9; i++) {
            const float a = bf_lo(cv[i]), b = bf_hi(cv[i]);
            sts32(bufA + (warp * BUFA_PITCH + 2 * (lane + 32 * i)) * 2,
                  pack_bf2(a * rcp(1.0f + ex2(-a * LOG2E)), b * rcp(1.0f + ex2(-b * LOG2E))));
        }
        if (crit) {
            unsigned mean2; float rsd;
            ln_stats(xw, mean2, rsd);
            if (lane == 0) sts64f(sb + SM_STAT + 8 * warp, bf_lo(mean2), rsd);
        }
        if (!crit) {
#pragma unroll
            for (int i = 0; i < 9; i++) {
                const int q = tid + 256 * i;
                const int r = q >> 2, ch = q & 1, tl = (q >> 1) & 1;
                cp_async16(sb + SM_WREG + tl * 18432 + r * 32 + ((ch ^ ((r >> 2) & 1)) << 4), prm.wmod + (size_t)r * 3456 + c00 + 8 * (q & 3));
            }
        } else if (c1 >= 0) {
#pragma unroll
            for (int i = 0; i < 5; i++) {
                const int q = tid + 256 * i;
                const int r = q >> 1, ch = q & 1;
                if (q < 1152) cp_async16(sb + SM_WREG + 18432 + r * 32 + ((ch ^ ((r >> 2) & 1)) << 4), prm.wmod + (size_t)r * 3456 + c1 + 8 * ch);
            }
        }
        asm volatile("cp.async.commit_group;" ::: "memory");
        asm volatile("cp.async.wait_group 1;" ::: "memory");
    }
    __syncthreads();
    const unsigned epoch = *s_epoch;
    TW(1);
    const int par = epoch & 1;
    const unsigned tag16 = epoch % 65535u + 1u;
    const unsigned tag2 = epoch % 3u + 1u;
    const unsigned tagR = (epoch % 0xffffffu + 1u) << 8;

    if (cta < NROLE) {
        uint32_t mb[5][2];
#pragma unroll
        for (int i = 0; i < 5; i++) {
            mb[i][0] = mb[i][1] = 0u;
            if (i < 4 || warp < 4) { mb[i][0] = lds32(bA + (warp + 8 * i) * 32); mb[i][1] = lds32(bA + (warp + 8 * i) * 32 + 16); }
        }
        auto mod_mma = [&](uint32_t tb, uint32_t red) {
            float acc[4] = {0.f, 0.f, 0.f, 0.f};
            const uint32_t ab = tb + kr * 32 + ((cs ^ ((kr >> 2) & 1)) << 4) + warp * 512;
            uint32_t a[5][4];
#pragma unroll
            for (int i = 0; i < 5; i++)
                if (i < 4 || warp < 4) ldsm4t(ab + i * 4096, a[i]);
#pragma unroll
            for (int i = 0; i < 5; i++)
                if (i < 4 || warp < 4) mma16816(acc, a[i], mb[i][0], mb[i][1]);
            sts128f(red + tid * 16, acc[0], acc[1], acc[2], acc[3]);
        };
        auto mod_sum = [&](uint32_t red) {
            float4 u[8];
#pragma unroll
            for (int k = 0; k < 8; k++) u[k] = lds128f(red + (k * 32 + lane) * 16);
            float4 v;
            v.x = ((u[0].x + u[1].x) + (u[2].x + u[3].x)) + ((u[4].x + u[5].x) + (u[6].x + u[7].x));
            v.y = ((u[0].y + u[1].y) + (u[2].y + u[3].y)) + ((u[4].y + u[5].y) + (u[6].y + u[7].y));
            v.z = ((u[0].z + u[1].z) + (u[2].z + u[3].z)) + ((u[4].z + u[5].z) + (u[6].z + u[7].z));
            v.w = ((u[0].w + u[1].w) + (u[2].w + u[3].w)) + ((u[4].w + u[5].w) + (u[6].w + u[7].w));
            return v;
        };
        auto mod_put = [&](const float4 v, int col) {
            stg_relaxed1(&g_mod[(2 * t) * 3456 + col + g], (bf_bits(v.x) << 16) | tag16);
            stg_relaxed1(&g_mod[(2 * t + 1) * 3456 + col + g], (bf_bits(v.y) << 16) | tag16);
            stg_relaxed1(&g_mod[(2 * t) * 3456 + col + 8 + g], (bf_bits(v.z) << 16) | tag16);
            stg_relaxed1(&g_mod[(2 * t + 1) * 3456 + col + 8 + g], (bf_bits(v.w) << 16) | tag16);
        };
        if (crit) mod_mma(sb + SM_WREG, sb + SM_RED);
        cons_sync();
        if (crit && warp == 0) {
            const float4 v = mod_sum(sb + SM_RED);
            const float4 st = lds128f(sb + SM_STAT + 16 * t);
            const float y0 = bfr(bfr(x0 - st.x) * st.y), y1 = bfr(bfr(x1 - st.z) * st.w);
            const float h0 = bfr(y0 * bfr(1.0f + bfr(v.z))) + bfr(v.x);
            const float h1 = bfr(y1 * bfr(1.0f + bfr(v.w))) + bfr(v.y);
            stg_relaxed1(&g_h[(2 * t) * DM + 8 * cta + g], (bf_bits(h0) << 16) | tag16);
            stg_relaxed1(&g_h[(2 * t + 1) * DM + 8 * cta + g], (bf_bits(h1) << 16) | tag16);
        }
        TS(1);
        TW(2);
        mbar_wait(bar_wq, 0);
        const int tile = warp & 1, kq = warp >> 1;
        uint32_t aq[9][4];
        {
            const uint32_t ab = sb + SM_WB + (144 * kq + kr) * 64 + (((2 * tile + cs) ^ ((kr >> 1) & 3)) << 4);
#pragma unroll
            for (int i = 0; i < 9; i++) ldsm4t(ab + i * 1024, aq[i]);
        }
        TW(3);
        uint2 hv[9];
        load_row16<9>(g_h + warp * DM, lane, hv);
        fix_row16<9>(g_h + warp * DM, lane, tag16, hv);
        __syncwarp();
        TW(4);
#pragma unroll
        for (int i = 0; i < 9; i++) sts32(bufA + (warp * BUFA_PITCH + 2 * (lane + 32 * i)) * 2, pack_hi(hv[i].x, hv[i].y));
        cons_sync();
        float acc0[4] = {0.f, 0.f, 0.f, 0.f}, acc1[4] = {0.f, 0.f, 0.f, 0.f};
#pragma unroll
        for (int i = 0; i < 9; i++) {
            const uint32_t b0 = lds32(bA + (9 * kq + i) * 32), b1 = lds32(bA + (9 * kq + i) * 32 + 16);
            if (i & 1) mma16816(acc1, aq[i], b0, b1); else mma16816(acc0, aq[i], b0, b1);
        }
        sts128f(sb + SM_RED + tid * 16, acc0[0] + acc1[0], acc0[1] + acc1[1], acc0[2] + acc1[2], acc0[3] + acc1[3]);
        asm volatile("fence.proxy.async.shared::cta;" ::: "memory");
        cons_sync();
        if (warp < 2) {
            float4 v = lds128f(sb + SM_RED + (warp * 32 + lane) * 16);
#pragma unroll
            for (int k = 1; k < 4; k++) { const float4 u = lds128f(sb + SM_RED + ((warp + 2 * k) * 32 + lane) * 16); v.x += u.x; v.y += u.y; v.z += u.z; v.w += u.w; }
            const int col = 32 * cta + 16 * warp + g;
            stg_relaxed1(&g_q[(2 * t) * 4096 + col], (bf_bits(v.x) << 16) | tag16);
            stg_relaxed1(&g_q[(2 * t + 1) * 4096 + col], (bf_bits(v.y) << 16) | tag16);
            stg_relaxed1(&g_q[(2 * t) * 4096 + col + 8], (bf_bits(v.z) << 16) | tag16);
            stg_relaxed1(&g_q[(2 * t + 1) * 4096 + col + 8], (bf_bits(v.w) << 16) | tag16);
        }
        TW(13);
        if (c1 >= 0) {
            asm volatile("cp.async.wait_group 0;" ::: "memory");
            cons_sync();
            if (!crit) mod_mma(sb + SM_WREG, sb + SM_RED2 + 4096);
            mod_mma(sb + SM_WREG + 18432, sb + SM_RED2);
            asm volatile("fence.proxy.async.shared::cta;" ::: "memory");
            cons_sync();
            if (warp == 2) mod_put(mod_sum(sb + SM_RED2), c1);
            if (warp == 3 && !crit) mod_put(mod_sum(sb + SM_RED2 + 4096), c00);
        }
    }
    TS(2);
    TW(5);
    unsigned cpk[9], spk[9];
    const int ocol = 16 * (cta >> 1) + 4 * (cta & 1) + ((tid >> 4) & 3) + 8 * ((tid >> 1) & 1);
    const int ob = 2 * ((tid >> 2) & 3) + (tid & 1);
    const bool oth = cta < NRED && tid < 64;
    unsigned gab = 0; float xin = 0.f;
#pragma unroll
    for (int i = 0; i < 9; i++) { cpk[i] = 0; spk[i] = 0; }

    const int grp = warp >> 2, wq = warp & 3;
    int n = grp;
    int nend = 0;
    unsigned cw0 = 0;
    {
        uint32_t kpre[2], vpre[2];
        {
            const int key = (lane & 7) + 8 * ((lane >> 3) & 1), kc = lane >> 4;
#pragma unroll
            for (int h = 0; h < 2; h++) {
                const int r = 2 * (16 * wq + key) + h;
                kpre[h] = r * 128 + ((kc ^ (r & 7)) << 4);
            }
            const int k7 = (lane & 7), hi = lane >> 4, cv = (lane >> 3) & 1;
            const int vkey = (k7 >> 1) + 8 * (k7 & 1) + 4 * hi;
#pragma unroll
            for (int h = 0; h < 2; h++) {
                const int r = 2 * (16 * wq + vkey) + h;
                vpre[h] = r * 128 + ((cv ^ (r & 7)) << 4);
            }
        }
        uint32_t qf[8][2];
        float o[8][4];
        float m = -INFINITY, l = 0.f;
        int cur = -1, cnt = 0;
        bool flushed = false, mod_done = cta >= NROLE;
#pragma unroll
        for (int i = 0; i < 8; i++) { qf[i][0] = qf[i][1] = 0; o[i][0] = o[i][1] = o[i][2] = o[i][3] = 0.f; }
        const uint32_t scr = sb + SM_BUFA + grp * 4096, sml = sb + SM_ML + grp * 64;
        for (;; n += 2) {
            const uint32_t ph = (n >> 2) & 1;
            mbar_wait(bar_ctrl + 8 * (n & 3), ph);
            const int np = meta[n & 3].x, fslot = meta[n & 3].y;
            if (!mod_done && (n >= NMOD || np < 0)) {
                mod_done = true;
                uint2 cbv[9], sbv[9];
                load_row16<9>(g_mod + warp * 3456 + 4 * DM, lane, cbv);
                load_row16<9>(g_mod + warp * 3456 + 3 * DM, lane, sbv);
                if (oth) {
                    unsigned gaw, gbw, spins = 0;
                    xin = __bfloat162float(prm.x[ob * DM + ocol]);
                    do {
                        gaw = ldg_relaxed1(&g_mod[ob * 3456 + 2 * DM + ocol]);
                        gbw = ldg_relaxed1(&g_mod[ob * 3456 + 5 * DM + ocol]);
                        if (++spins > SPIN_LIMIT) TRAP_AT(__LINE__);
                    } while ((gaw & 0xffffu) != tag16 || (gbw & 0xffffu) != tag16);
                    gab = pack_hi(gaw, gbw);
                }
                fix_row16<9>(g_mod + warp * 3456 + 4 * DM, lane, tag16, cbv);
                fix_row16<9>(g_mod + warp * 3456 + 3 * DM, lane, tag16, sbv);
#pragma unroll
                for (int i = 0; i < 9; i++) {
                    cpk[i] = pack_bf2(1.0f + bf_hi(cbv[i].x), 1.0f + bf_hi(cbv[i].y));
                    spk[i] = pack_hi(sbv[i].x, sbv[i].y);
                }
            }
            if (np != cur) {
                uint2 qa[8], qb2[8];
                const unsigned* qb = g_q + ((np < 0 ? 0 : np) >> 4) * 4096 + ((np < 0 ? 0 : np) & 15) * 256 + (g & 1) * 128 + 2 * t;
                if (np >= 0) {
#pragma unroll
                    for (int ks = 0; ks < 8; ks++) { qa[ks] = ldg_relaxed2(qb + 16 * ks); qb2[ks] = ldg_relaxed2(qb + 16 * ks + 8); }
                } else {
                    cw0 = ldg_relaxed1(&g_ctr[par][warp * 16 + ((cta >> 3) & 15)]);
                    TW(8);
                }
                if (cur >= 0) {
                    if (flushed) group_sync(grp);
                    flushed = true;
                    if (t == 0) {
                        const uint32_t so = scr + wq * 1024 + g * 8;
#pragma unroll
                        for (int mt = 0; mt < 8; mt++) {
                            sts64f(so + mt * 128, o[mt][0], o[mt][1]);
                            sts64f(so + mt * 128 + 64, o[mt][2], o[mt][3]);
                        }
                    }
#pragma unroll
                    for (int of = 4; of <= 16; of <<= 1) l += __shfl_xor_sync(0xffffffffu, l, of);
                    if (lane < 2) sts64f(sml + wq * 16 + lane * 8, m, l);
                    group_sync(grp);
                    {
                        const int d = tid & 127;
                        unsigned long long* rec = g_part + ((size_t)(2 * fslot + grp) * NPAIR + cur) * RSTRIDE;
                        float4 ml[4]; float2 ov[4];
#pragma unroll
                        for (int w = 0; w < 4; w++) { ml[w] = lds128f(sml + w * 16); ov[w] = lds64f(scr + w * 1024 + d * 8); }
                        const float M0 = fmaxf(fmaxf(ml[0].x, ml[1].x), fmaxf(ml[2].x, ml[3].x));
                        const float M1 = fmaxf(fmaxf(ml[0].z, ml[1].z), fmaxf(ml[2].z, ml[3].z));
                        float O0 = 0.f, O1 = 0.f, L0 = 0.f, L1 = 0.f;
#pragma unroll
                        for (int w = 0; w < 4; w++) {
                            const float f0 = ex2((ml[w].x - M0) * LOG2E), f1 = ex2((ml[w].z - M1) * LOG2E);
                            O0 = fmaf(f0, ov[w].x, O0); O1 = fmaf(f1, ov[w].y, O1);
                            L0 = fmaf(f0, ml[w].y, L0); L1 = fmaf(f1, ml[w].w, L1);
                        }
                        stg_relaxed64x2(rec + 2 * d, tagged(O0, tagR), tagged(O1, tagR));
                        if (d < 2) stg_relaxed64x2(rec + 256 + 2 * d, tagged(d ? M1 : M0, tagR), tagged(d ? L1 : L0, tagR | (unsigned)cnt));
                    }
                }
                if (np < 0) { nend = -1 - np; break; }
                cur = np; cnt = 0;
                m = -INFINITY; l = 0.f;
#pragma unroll
                for (int mt = 0; mt < 8; mt++) { o[mt][0] = o[mt][1] = o[mt][2] = o[mt][3] = 0.f; }
                unsigned spins = 0;
                while (true) {
                    bool ok = true;
#pragma unroll
                    for (int ks = 0; ks < 8; ks++) {
                        ok = ok && ((qa[ks].x & 0xffffu) == tag16) && ((qa[ks].y & 0xffffu) == tag16) &&
                             ((qb2[ks].x & 0xffffu) == tag16) && ((qb2[ks].y & 0xffffu) == tag16);
                    }
                    if (__all_sync(0xffffffffu, ok)) break;
                    if (++spins > SPIN_LIMIT) TRAP_AT(__LINE__);
#pragma unroll
                    for (int ks = 0; ks < 8; ks++) { qa[ks] = ldg_relaxed2(qb + 16 * ks); qb2[ks] = ldg_relaxed2(qb + 16 * ks + 8); }
                }
#pragma unroll
                for (int ks = 0; ks < 8; ks++) { qf[ks][0] = pack_hi(qa[ks].x, qa[ks].y); qf[ks][1] = pack_hi(qb2[ks].x, qb2[ks].y); }
            }
            if (n == 0) TS(3);
            if (n < 2) TW(6);
            if (n == 4 || n == 5) TW(7);
            if (n == 4) TS(4);
            const int sK = (2 * n) & 7;
            const uint32_t kb = sb + SM_RING + sK * TILE, vb = kb + TILE;
            mbar_wait(bar_full + 8 * sK, ph);
            float c0[4] = {0.f, 0.f, 0.f, 0.f}, c1a[4] = {0.f, 0.f, 0.f, 0.f};
#pragma unroll
            for (int ks = 0; ks < 8; ks += 2) {
                uint32_t a[4], b[4];
                ldsm4(kb + (kpre[ks >> 2] ^ ((ks & 3) << 5)), a);
                ldsm4(kb + (kpre[(ks + 1) >> 2] ^ (((ks + 1) & 3) << 5)), b);
                mma16816(c0, a, qf[ks][0], qf[ks][1]);
                mma16816(c1a, b, qf[ks + 1][0], qf[ks + 1][1]);
            }
            __syncwarp();
            if (lane == 0) mbar_arrive(bar_empty + 8 * sK);
            float s0 = (t & 1) ? (c0[1] + c1a[1]) : (c0[0] + c1a[0]);
            float s1 = (t & 1) ? (c0[3] + c1a[3]) : (c0[2] + c1a[2]);
            s0 = bfr(bfr(s0) * QSCALE);
            s1 = bfr(bfr(s1) * QSCALE);
            float bm = fmaxf(s0, s1);
            if (__any_sync(0xffffffffu, bm > m)) {
#pragma unroll
                for (int of = 4; of <= 16; of <<= 1) bm = fmaxf(bm, __shfl_xor_sync(0xffffffffu, bm, of));
                const float mn = fmaxf(m, bm);
                const float al = ex2((m - mn) * LOG2E);
                m = mn; l *= al;
                const float alo = __shfl_xor_sync(0xffffffffu, al, 1);
                const float a0 = (t & 1) ? alo : al, a1 = (t & 1) ? al : alo;
#pragma unroll
                for (int mt = 0; mt < 8; mt++) { o[mt][0] *= a0; o[mt][1] *= a1; o[mt][2] *= a0; o[mt][3] *= a1; }
            }
            const float p0 = ex2((s0 - m) * LOG2E), p1 = ex2((s1 - m) * LOG2E);
            l += p0 + p1;
            const unsigned pk = pack_bf2(p0, p1);
            const unsigned pb0 = __shfl_sync(0xffffffffu, pk, 4 * t + (g & 1));
            const unsigned pb1 = __shfl_sync(0xffffffffu, pk, 4 * (t + 4) + (g & 1));
            mbar_wait(bar_full + 8 * (sK + 1), ph);
#pragma unroll
            for (int mt = 0; mt < 8; mt++) {
                uint32_t a[4];
                ldsm4t(vb + (vpre[mt >> 2] ^ ((mt & 3) << 5)), a);
                mma16816(o[mt], a, pb0, pb1);
            }
            __syncwarp();
            if (lane == 0) mbar_arrive(bar_empty + 8 * (sK + 1));
            cnt++;
        }
    }
    TS(5);
    TW(9);
    TS2(15);
    if (threadIdx.x == 0) TSV(16, 2 * nend + 2);
    if (cta >= NROLE) return;

    uint32_t sl[6];
#pragma unroll
    for (int i = 0; i < 6; i++) sl[i] = sb + SM_RING + ((2 * nend + i) & 7) * TILE;
    const uint32_t bACT = sb + SM_ACT + (g * ACT_PITCH + 2 * t) * 2;
    const uint32_t wsw = (uint32_t)(warp >> 2);
    {
        uint32_t aw[5][2][4];
        bool wo_ok = false;
        auto wo_frag = [&]() {
            const uint32_t ab = sb + SM_WREG + wsw * 2048 + kr * 128 + ((((warp & 3) * 2 + cs) ^ (kr & 7)) << 4);
#pragma unroll
            for (int i = 0; i < 5; i++)
                if (i < 4 || warp < 4) { ldsm4t(ab + i * 4096, aw[i][0]); ldsm4t(ab + i * 4096 + 9 * 2048, aw[i][1]); }
            wo_ok = true;
            TW(10);
        };
        constexpr size_t RS = (size_t)NPAIR * RSTRIDE;
        const int d0 = (cta & 7) * 16, half = lane >> 4;
        const unsigned long long* rec = g_part + (size_t)(warp * 16 + (cta >> 3)) * RSTRIDE;
        const unsigned* ctr = &g_ctr[par][warp * 16 + (cta >> 3)];
        int nv = (int)(__shfl_sync(0xffffffffu, cw0, 0) >> 16) + 1;
        float val;
        {
            const unsigned long long* pd = rec + half * RS + 2 * (d0 + (lane & 15));
            const unsigned long long* ph = rec + (lane >> 1) * RS + 256 + 2 * (lane & 1);
            ulonglong2 w[8], hd = make_ulonglong2(0ull, 0ull);
#pragma unroll
            for (int i = 0; i < 8; i++) w[i] = make_ulonglong2(0ull, 0ull);
            unsigned got = 0, pm = 0, spins = 0;
            bool hok = false;
            while (nv <= 8) {
                if (!hok && (lane >> 2) < nv) hd = ldg_relaxed64x2(ph);
#pragma unroll
                for (int i = 0; i < 8; i++)
                    if (i < nv) ldg_relaxed64x2_p(w[i], pd + 2 * i * RS, !((got >> (4 * i)) & 1u));
                cw0 = ldg_relaxed1(ctr);
                if (!wo_ok && __all_sync(0xffffffffu, mbar_test(bar_wo + 8 * min(lane, 2), 0))) wo_frag();
                hok = (unsigned)hd.x == tagR && ((unsigned)hd.y & ~0xffu) == tagR;
#pragma unroll
                for (int i = 0; i < 8; i++)
                    if ((unsigned)w[i].x == tagR && (unsigned)w[i].y == tagR) got |= 1u << (4 * i);
                const unsigned vm = __ballot_sync(0xffffffffu, hok);
                pm = vm & (vm >> 1) & 0x55555555u;
                const unsigned tot = __reduce_add_sync(0xffffffffu, ((pm >> lane) & 1u) ? ((unsigned)hd.y & 0xffu) : 0u);
                const bool ok = ((pm >> (2 * half)) & 0x11111111u & ~got) == 0u;
                if (tot == (unsigned)UNITS && __all_sync(0xffffffffu, ok)) break;
                nv = (int)(__shfl_sync(0xffffffffu, cw0, 0) >> 16) + 1;
                if (++spins > SPIN_LIMIT) TRAP_AT(__LINE__);
            }
            if (nv > 8) {
                val = combine_slow(rec, ctr, d0, tagR, lane);
            } else {
            if (threadIdx.x == 0) { TSV(14, 2 * nv); TSV(22, spins); }
            TS(21);
            TW(11);
            const bool sv = (pm >> (lane & ~1)) & 1u;
            const unsigned mb = (unsigned)(hd.x >> 32);
            const unsigned key = sv ? (mb ^ ((mb >> 31) ? 0xffffffffu : 0x80000000u)) : 0u;
            const unsigned k0 = __reduce_max_sync(0xffffffffu, (lane & 1) ? 0u : key);
            const unsigned k1 = __reduce_max_sync(0xffffffffu, (lane & 1) ? key : 0u);
            const unsigned kM = (lane & 1) ? k1 : k0;
            const float M = __uint_as_float(kM ^ ((kM >> 31) ? 0x80000000u : 0xffffffffu));
            const float f = sv ? ex2((__uint_as_float(mb) - M) * LOG2E) : 0.f;
            const uint32_t fs = sb + SM_RED + warp * 128;
            sts32(fs + ((((lane >> 1) & 1) * 16 + (lane >> 2) * 2 + (lane & 1)) << 2), __float_as_uint(f));
            float L = sv ? f * __uint_as_float((unsigned)(hd.y >> 32)) : 0.f;
            __syncwarp();
            float4 ff[4];
#pragma unroll
            for (int i = 0; i < 4; i++) ff[i] = lds128f(fs + half * 64 + i * 16);
#pragma unroll
            for (int of = 2; of <= 16; of <<= 1) L += __shfl_xor_sync(0xffffffffu, L, of);
            float a0 = 0.f, a1 = 0.f;
#pragma unroll
            for (int i = 0; i < 8; i++) {
                const float f0 = (i & 1) ? ff[i >> 1].z : ff[i >> 1].x, f1 = (i & 1) ? ff[i >> 1].w : ff[i >> 1].y;
                a0 = fmaf(f0, f0 != 0.f ? __uint_as_float((unsigned)(w[i].x >> 32)) : 0.f, a0);
                a1 = fmaf(f1, f1 != 0.f ? __uint_as_float((unsigned)(w[i].y >> 32)) : 0.f, a1);
            }
            const float v = (half ? a1 : a0) + __shfl_xor_sync(0xffffffffu, half ? a0 : a1, 16);
            val = __fdividef(v, __shfl_sync(0xffffffffu, L, half));
            }
        }
        sts16(sb + SM_ACT + (warp * ACT_PITCH + lane) * 2, bf_bits(val));
        TW(12);
        if (!wo_ok) {
            for (int i = 0; i < 3; i++) mbar_wait(bar_wo + 8 * i, 0);
            wo_frag();
        }
        cons_sync();
        TS(6);
        const uint32_t b00 = lds32(bACT), b01 = lds32(bACT + 16), b10 = lds32(bACT + 32), b11 = lds32(bACT + 48);
        unsigned* dst = g_wop + (size_t)cta * (DM * NB) + warp * 128 + lane * 4;
#pragma unroll
        for (int i = 0; i < 5; i++) {
            if (i < 4 || warp < 4) {
                float acc[4] = {0.f, 0.f, 0.f, 0.f};
                mma16816(acc, aw[i][0], b00, b01);
                mma16816(acc, aw[i][1], b10, b11);
                put_partial(dst + i * 1024, acc, tag2);
            }
        }
    }
    TS(17);
    TW(14);
    const int kq = warp & 3, tg = warp >> 2;
    uint32_t ag[3][9][4];
    if (cta < NRED) {
        uint4 rv[8];
        const unsigned* rp = red_ptr(g_wop, cta, warp, lane);
        red_issue(rp, rv);
        const float s = red_finish(rp, rv, tag2, sb, tid, 16);
        TS(19);
        if (tid < 64) {
            xin = bfr(xin + bfr(bf_lo(gab) * bfr(s)));
            const unsigned me = bf_bits(xin), other = __shfl_xor_sync(0xffffffffu, me, 16);
            if (lane < 16) stg_relaxed1(&g_x2[ob * (DM / 2) + (ocol >> 1)], (me | (other << 16)) + 1u);
        }
    }
    TW(17);
    {
#pragma unroll
        for (int i = 0; i < 3; i++) {
            mbar_wait(bar_gate + 8 * i, 0);
            mbar_wait(bar_full + 8 * ((2 * nend + i) & 7), ((2 * nend + i) >> 3) & 1);
        }
#pragma unroll
        for (int i = 0; i < 9; i++) {
            const int r0 = 144 * kq + 16 * i;
            const int box = r0 / 192;
            const uint32_t base = cs ? (sb + SM_RING + ((2 * nend + box) & 7) * TILE) : (sb + SM_WB + box * 15360);
            const uint32_t ab = base + (r0 - 192 * box + kr) * 80 + tg * 48;
            ldsm4t(ab, ag[0][i]);
            ldsm4t(ab + 16, ag[1][i]);
        }
        TW(15);
    }
    TS(8);
    if (tg == 0) {
#pragma unroll
        for (int i = 0; i < 9; i++) {
            const int r0 = 144 * kq + 16 * i;
            const int box = r0 / 192;
            const uint32_t base = cs ? (sb + SM_RING + ((2 * nend + box) & 7) * TILE) : (sb + SM_WB + box * 15360);
            ldsm4t(base + (r0 - 192 * box + kr) * 80 + 32, ag[2][i]);
        }
    }
    {
        unsigned xw[9];
        const unsigned* xp = g_x2 + warp * (DM / 2) + lane;
#pragma unroll
        for (int i = 0; i < 9; i++) xw[i] = ldg_relaxed1(xp + 32 * i);
        unsigned spins = 0;
        while (true) {
            bool ok = true;
#pragma unroll
            for (int i = 0; i < 9; i++)
                if (xw[i] == 0u) { xw[i] = ldg_relaxed1(xp + 32 * i); ok = false; }
            if (ok) break;
            if (++spins > SPIN_LIMIT) TRAP_AT(__LINE__);
        }
        __syncwarp();
        TS(20);
        TW(18);
#pragma unroll
        for (int i = 0; i < 9; i++) xw[i] -= 1u;
        unsigned mean2; float rsd;
        ln_stats(xw, mean2, rsd);
#pragma unroll
        for (int i = 0; i < 9; i++)
            sts32(bufA + (warp * BUFA_PITCH + 2 * (lane + 32 * i)) * 2, ln_apply(xw[i], mean2, rsd, cpk[i], spk[i]));
    }
    TW(19);
    cons_sync();
    TS(9);
    const uint32_t gred = sb + SM_RING + ((2 * nend + 6) & 7) * TILE;
    {
        float acc[3][4];
#pragma unroll
        for (int j = 0; j < 3; j++) acc[j][0] = acc[j][1] = acc[j][2] = acc[j][3] = 0.f;
#pragma unroll
        for (int i = 0; i < 9; i++) {
            const uint32_t b0 = lds32(bA + (9 * kq + i) * 32), b1 = lds32(bA + (9 * kq + i) * 32 + 16);
            mma16816(acc[0], ag[0][i], b0, b1);
            mma16816(acc[1], ag[1][i], b0, b1);
            if (tg == 0) mma16816(acc[2], ag[2][i], b0, b1);
        }
        const uint32_t ga = gred + ((kq * 5 + tg * 3) * 32 + lane) * 16;
        sts128f(ga, acc[0][0], acc[0][1], acc[0][2], acc[0][3]);
        sts128f(ga + 512, acc[1][0], acc[1][1], acc[1][2], acc[1][3]);
        if (tg == 0) sts128f(ga + 1024, acc[2][0], acc[2][1], acc[2][2], acc[2][3]);
    }
    TW(20);
    uint32_t ad[5][3][4];
    {
#pragma unroll
        for (int i = 3; i < 6; i++) mbar_wait(bar_full + 8 * ((2 * nend + i) & 7), ((2 * nend + i) >> 3) & 1);
#pragma unroll
        for (int ks = 0; ks < 3; ks++) {
            const int r = min(16 * ks + kr, 35);
            const uint32_t off = r * 128 + ((((warp & 3) * 2 + cs) ^ (r & 7)) << 4);
#pragma unroll
            for (int i = 0; i < 5; i++) {
                if (i < 4 || warp < 4) {
                    const int cb0 = 2 * i, cb1 = 2 * i + 1;
                    const uint32_t bx = wsw ? (sl[3 + (cb1 / 3 > 2 ? 2 : cb1 / 3)] + (cb1 % 3) * 5120) : (sl[3 + cb0 / 3] + (cb0 % 3) * 5120);
                    ldsm4t(bx + off, ad[i][ks]);
                }
            }
        }
    }
    TW(21);
    cons_sync();
    if (tid < 160) {
        const uint32_t ga = gred + tid * 16;
        float4 v = lds128f(ga);
#pragma unroll
        for (int k = 1; k < 4; k++) { const float4 u = lds128f(ga + k * 2560); v.x += u.x; v.y += u.y; v.z += u.z; v.w += u.w; }
        const int cl = 8 * warp + g - 4 * (cta & 1);
#pragma unroll
        for (int e = 0; e < 2; e++) {
            const float gt = bfr(e ? v.y : v.x), up = bfr(e ? v.w : v.z);
            const float inner = 0.7978845608028654f * fmaf(0.044715f * gt * gt, gt, gt);
            const float ge = bfr(gt * rcp(1.0f + ex2(inner * (-2.0f * LOG2E))));
            if (cl >= 0 && cl < 36) sts16(sb + SM_ACT + ((2 * t + e) * ACT_PITCH + cl) * 2, bf_bits(ge * up));
        }
    }
    TW(22);
    cons_sync();
    TS(10);
    {
        uint32_t b[3][2];
#pragma unroll
        for (int ks = 0; ks < 3; ks++) { b[ks][0] = lds32(bACT + ks * 32); b[ks][1] = lds32(bACT + ks * 32 + 16); }
        unsigned* dst = g_dnp + (size_t)cta * (DM * NB) + warp * 128 + lane * 4;
#pragma unroll
        for (int i = 0; i < 5; i++) {
            if (i < 4 || warp < 4) {
                float acc[4] = {0.f, 0.f, 0.f, 0.f};
#pragma unroll
                for (int ks = 0; ks < 3; ks++) mma16816(acc, ad[i][ks], b[ks][0], b[ks][1]);
                put_partial(dst + i * 1024, acc, tag2);
            }
        }
    }
    TS(11);
    TW(24);
    if (cta < NRED) {
        uint4 rv[8];
        const unsigned* rp = red_ptr(g_dnp, cta, warp, lane);
        red_issue(rp, rv);
        const float s = red_finish(rp, rv, tag2, sb, tid, 25);
        if (tid < 64) prm.out[ob * DM + ocol] = __float2bfloat16_rn(xin + bfr(bf_hi(gab) * bfr(s)));
    }
    TS(12);
    TW(26);
}

typedef CUresult (*EncodeFn)(CUtensorMap*, CUtensorMapDataType, cuuint32_t, void*, const cuuint64_t*, const cuuint64_t*,
                             const cuuint32_t*, const cuuint32_t*, CUtensorMapInterleave, CUtensorMapSwizzle,
                             CUtensorMapL2promotion, CUtensorMapFloatOOBfill);

bool make_map(EncodeFn fn, CUtensorMap* m, const void* ptr, uint64_t inner, uint64_t outer, uint64_t stride_bytes,
              uint32_t box_inner, uint32_t box_outer, CUtensorMapSwizzle sw, CUtensorMapL2promotion promo) {
    cuuint64_t dims[2] = {inner, outer};
    cuuint64_t strides[1] = {stride_bytes};
    cuuint32_t box[2] = {box_inner, box_outer};
    cuuint32_t es[2] = {1, 1};
    return fn(m, CU_TENSOR_MAP_DATA_TYPE_BFLOAT16, 2, const_cast<void*>(ptr), dims, strides, box, es,
              CU_TENSOR_MAP_INTERLEAVE_NONE, sw, promo, CU_TENSOR_MAP_FLOAT_OOB_FILL_NONE) == CUDA_SUCCESS;
}

}

extern "C" void kernel_launch(void* const* d_in, const int* in_sizes, int n_in, void* d_out, int out_size) {
    (void)in_sizes; (void)n_in; (void)out_size;
    static EncodeFn encode = nullptr;
    static int num_sms = 0;
    if (!encode) {
        void* fn = nullptr;
        cudaDriverEntryPointQueryResult qres;
        cudaGetDriverEntryPoint("cuTensorMapEncodeTiled", &fn, cudaEnableDefault, &qres);
        encode = (EncodeFn)fn;
        int dev = 0;
        cudaGetDevice(&dev);
        cudaDeviceGetAttribute(&num_sms, cudaDevAttrMultiProcessorCount, dev);
        cudaFuncSetAttribute(fused_kernel, cudaFuncAttributeMaxDynamicSharedMemorySize, SMEM_BYTES);
    }
    CUtensorMap tmK, tmV, tmQ, tmO, tmG, tmU, tmD;
    const uint64_t kvrows = (uint64_t)NPAIR * SK * 2;
    make_map(encode, &tmK, d_in[1], 64, kvrows, 128, 64, 128, CU_TENSOR_MAP_SWIZZLE_128B, CU_TENSOR_MAP_L2_PROMOTION_L2_256B);
    make_map(encode, &tmV, d_in[2], 64, kvrows, 128, 64, 128, CU_TENSOR_MAP_SWIZZLE_128B, CU_TENSOR_MAP_L2_PROMOTION_L2_256B);
    make_map(encode, &tmQ, d_in[3], 4096, DM, 8192, 32, 192, CU_TENSOR_MAP_SWIZZLE_64B, CU_TENSOR_MAP_L2_PROMOTION_L2_128B);
#define WPROMO CU_TENSOR_MAP_L2_PROMOTION_L2_128B
    make_map(encode, &tmO, d_in[4], DM, 4096, DM * 2, 64, 16, CU_TENSOR_MAP_SWIZZLE_128B, WPROMO);
    make_map(encode, &tmG, d_in[6], FF, DM, FF * 2, 40, 192, CU_TENSOR_MAP_SWIZZLE_NONE, WPROMO);
    make_map(encode, &tmU, d_in[7], FF, DM, FF * 2, 40, 192, CU_TENSOR_MAP_SWIZZLE_NONE, WPROMO);
    make_map(encode, &tmD, d_in[8], DM, FF, DM * 2, 64, 36, CU_TENSOR_MAP_SWIZZLE_128B, WPROMO);
    Params prm;
    prm.x = (const __nv_bfloat16*)d_in[0];
    prm.c = (const __nv_bfloat16*)d_in[9];
    prm.wmod = (const __nv_bfloat16*)d_in[10];
    prm.out = (__nv_bfloat16*)d_out;
    int grid = num_sms < MAXCTA ? num_sms : MAXCTA;
    fused_kernel<<<grid, NTHREADS, SMEM_BYTES>>>(tmK, tmV, tmQ, tmO, tmG, tmU, tmD, prm);
}
```

```cpp
#include <cuda_runtime.h>
#include <cuda_bf16.h>
#include <cuda.h>
#include <stdint.h>

namespace {

constexpr int NB = 8;
constexpr int DM = 576;
constexpr int SK = 8192;
constexpr int FF = 4608;
constexpr int NPAIR = 128;
constexpr int UKEYS = 64;
constexpr int UNITS = SK / UKEYS;
constexpr int U0 = 4;
constexpr int TILE = 16384;
constexpr int NTILE = 8;
#define INFL 4
#define INFL0 2
#define NRAMP 8
#define TINFL 2
#define WSTART 6
#define NCLR 48
#define NMOD 16
#define JD 6
#define DBGN 20
#define KVGATE 2
#define WEARLY 6
#define WQD 1
#define NCD 1200
constexpr int NROLE = 128;
constexpr int NRED = 72;
constexpr int MAXCTA = 132;
constexpr int RSTRIDE = 272;
constexpr int NTHREADS = 288;

constexpr int SM_RING = 0;
constexpr int SM_WREG = NTILE * TILE;
constexpr int SM_WB = SM_WREG + 36864;
constexpr int SM_BUFA = SM_WREG + 82944;
constexpr int BUFA_PITCH = 584;
constexpr int SM_RED = SM_BUFA + 8 * BUFA_PITCH * 2;
constexpr int SM_ACT = SM_RED + 4096;
constexpr int ACT_PITCH = 56;
constexpr int SM_ML = SM_ACT + 8 * ACT_PITCH * 2;
constexpr int SM_STAT = SM_ML + 128;
constexpr int SM_META = SM_STAT + 64;
constexpr int SM_BAR = SM_META + 32;
constexpr int SM_EPOCH = SM_BAR + 28 * 8;
constexpr int SM_SC = SM_EPOCH + 16;
constexpr int SM_TOTAL = SM_SC + 1280;
constexpr int SMEM_BYTES = SM_TOTAL + 1024;

__device__ __align__(128) unsigned g_tk[2][32];
__device__ __align__(128) unsigned g_cf[NPAIR * 8];
__device__ unsigned g_epoch;
__device__ unsigned g_started[2];
__device__ __align__(16) unsigned g_h[NB * DM];
__device__ __align__(16) unsigned g_mod[NB * 6 * DM];
__device__ __align__(16) unsigned g_q[NB * 4096];
__device__ __align__(128) unsigned long long g_part[(size_t)16 * UNITS * RSTRIDE];
__device__ __align__(128) unsigned g_wop[(size_t)NROLE * DM * NB];
__device__ __align__(128) unsigned g_x2[NB * DM / 2];
__device__ __align__(128) unsigned g_dnp[(size_t)NROLE * DM * NB];

struct Params {
    const __nv_bfloat16* x;
    const __nv_bfloat16* c;
    const __nv_bfloat16* wmod;
    __nv_bfloat16* out;
};

#define TRAP_AT(line) __trap()
#define TS(i)
#define TSL(i)
#define TS2(i)
#define TSP(i)
#define TSG(i, thr)
#define TSV(i, v)
#define TW(i)

__device__ __forceinline__ uint32_t smem_u32(const void* p) { return (uint32_t)__cvta_generic_to_shared(p); }
__device__ __forceinline__ void mbar_init(uint32_t bar, uint32_t cnt) {
    asm volatile("mbarrier.init.shared::cta.b64 [%0], %1;" ::"r"(bar), "r"(cnt) : "memory");
}
__device__ __forceinline__ void mbar_expect_tx(uint32_t bar, uint32_t bytes) {
    asm volatile("mbarrier.arrive.expect_tx.shared::cta.b64 _, [%0], %1;" ::"r"(bar), "r"(bytes) : "memory");
}
__device__ __forceinline__ void mbar_arrive(uint32_t bar) {
    asm volatile("mbarrier.arrive.shared::cta.b64 _, [%0];" ::"r"(bar) : "memory");
}
__device__ __forceinline__ bool mbar_try(uint32_t bar, uint32_t parity) {
    uint32_t ok;
    asm volatile(
        "{\n.reg .pred p;\n"
        "mbarrier.try_wait.parity.shared::cta.b64 p, [%1], %2;\n"
        "selp.u32 %0, 1, 0, p;\n}\n"
        : "=r"(ok) : "r"(bar), "r"(parity) : "memory");
    return ok != 0;
}
__device__ __forceinline__ bool mbar_test(uint32_t bar, uint32_t parity) {
    uint32_t ok;
    asm volatile(
        "{\n.reg .pred p;\n"
        "mbarrier.test_wait.parity.shared::cta.b64 p, [%1], %2;\n"
        "selp.u32 %0, 1, 0, p;\n}\n"
        : "=r"(ok) : "r"(bar), "r"(parity) : "memory");
    return ok != 0;
}
__device__ __noinline__ void mbar_wait_slow(uint32_t bar, uint32_t parity) {
    unsigned long long t0, t1;
    asm volatile("mov.u64 %0, %globaltimer;" : "=l"(t0));
    while (!mbar_try(bar, parity)) {
        asm volatile("mov.u64 %0, %globaltimer;" : "=l"(t1));
        if (t1 - t0 > 2000000000ull) TRAP_AT(__LINE__);
    }
}
__device__ __forceinline__ void mbar_wait(uint32_t bar, uint32_t parity) {
    if (!mbar_try(bar, parity)) mbar_wait_slow(bar, parity);
}
__device__ __forceinline__ void tma2d(uint32_t dst, const CUtensorMap* map, int c0, int c1, uint32_t bar) {
    asm volatile(
        "cp.async.bulk.tensor.2d.shared::cluster.global.mbarrier::complete_tx::bytes [%0], [%1, {%3, %4}], [%2];"
        ::"r"(dst), "l"((uint64_t)map), "r"(bar), "r"(c0), "r"(c1) : "memory");
}
__device__ __forceinline__ void tma2d_s(uint32_t dst, const CUtensorMap* map, int c0, int c1, uint32_t bar, uint64_t pol) {
    asm volatile(
        "cp.async.bulk.tensor.2d.shared::cluster.global.mbarrier::complete_tx::bytes.L2::cache_hint [%0], [%1, {%3, %4}], [%2], %5;"
        ::"r"(dst), "l"((uint64_t)map), "r"(bar), "r"(c0), "r"(c1), "l"(pol) : "memory");
}
__device__ __forceinline__ void prefetch_map(const CUtensorMap* map) {
    asm volatile("prefetch.tensormap [%0];" ::"l"((uint64_t)map) : "memory");
}
__device__ __forceinline__ void cp_async16(uint32_t dst, const void* src) {
    asm volatile("cp.async.cg.shared.global [%0], [%1], 16;" ::"r"(dst), "l"(src) : "memory");
}
__device__ __forceinline__ void ldsm4(uint32_t addr, uint32_t (&r)[4]) {
    asm volatile("ldmatrix.sync.aligned.m8n8.x4.shared.b16 {%0,%1,%2,%3}, [%4];"
                 : "=r"(r[0]), "=r"(r[1]), "=r"(r[2]), "=r"(r[3]) : "r"(addr) : "memory");
}
__device__ __forceinline__ void ldsm2(uint32_t addr, uint32_t& r0, uint32_t& r1) {
    asm volatile("ldmatrix.sync.aligned.m8n8.x2.shared.b16 {%0,%1}, [%2];" : "=r"(r0), "=r"(r1) : "r"(addr) : "memory");
}
__device__ __forceinline__ void ldsm4t(uint32_t addr, uint32_t (&r)[4]) {
    asm volatile("ldmatrix.sync.aligned.m8n8.x4.trans.shared.b16 {%0,%1,%2,%3}, [%4];"
                 : "=r"(r[0]), "=r"(r[1]), "=r"(r[2]), "=r"(r[3]) : "r"(addr) : "memory");
}
__device__ __forceinline__ void mma16816(float (&c)[4], const uint32_t (&a)[4], uint32_t b0, uint32_t b1) {
    asm volatile(
        "mma.sync.aligned.m16n8k16.row.col.f32.bf16.bf16.f32 {%0,%1,%2,%3}, {%4,%5,%6,%7}, {%8,%9}, {%0,%1,%2,%3};"
        : "+f"(c[0]), "+f"(c[1]), "+f"(c[2]), "+f"(c[3])
        : "r"(a[0]), "r"(a[1]), "r"(a[2]), "r"(a[3]), "r"(b0), "r"(b1));
}
__device__ __forceinline__ void cons_sync() { asm volatile("bar.sync 1, 256;" ::: "memory"); }
__device__ __forceinline__ void group_sync(int grp) { asm volatile("bar.sync %0, 128;" ::"r"(2 + grp) : "memory"); }
__device__ __forceinline__ uint32_t lds32(uint32_t addr) {
    uint32_t v; asm volatile("ld.shared.u32 %0, [%1];" : "=r"(v) : "r"(addr) : "memory"); return v;
}
__device__ __forceinline__ float2 lds64f(uint32_t addr) {
    float2 v; asm volatile("ld.shared.v2.f32 {%0,%1}, [%2];" : "=f"(v.x), "=f"(v.y) : "r"(addr) : "memory"); return v;
}
__device__ __forceinline__ float4 lds128f(uint32_t addr) {
    float4 v; asm volatile("ld.shared.v4.f32 {%0,%1,%2,%3}, [%4];" : "=f"(v.x), "=f"(v.y), "=f"(v.z), "=f"(v.w) : "r"(addr) : "memory"); return v;
}
__device__ __forceinline__ void sts32(uint32_t addr, unsigned v) {
    asm volatile("st.shared.u32 [%0], %1;" ::"r"(addr), "r"(v) : "memory");
}
__device__ __forceinline__ void sts16(uint32_t addr, unsigned v) {
    asm volatile("st.shared.u16 [%0], %1;" ::"r"(addr), "h"((unsigned short)v) : "memory");
}
__device__ __forceinline__ uint2 lds64u(uint32_t addr) {
    uint2 v; asm volatile("ld.shared.v2.u32 {%0,%1}, [%2];" : "=r"(v.x), "=r"(v.y) : "r"(addr) : "memory"); return v;
}
__device__ __forceinline__ void sts64f(uint32_t addr, float a, float b) {
    asm volatile("st.shared.v2.f32 [%0], {%1,%2};" ::"r"(addr), "f"(a), "f"(b) : "memory");
}
__device__ __forceinline__ void sts128f(uint32_t addr, float a, float b, float c, float d) {
    asm volatile("st.shared.v4.f32 [%0], {%1,%2,%3,%4};" ::"r"(addr), "f"(a), "f"(b), "f"(c), "f"(d) : "memory");
}
__device__ __forceinline__ uint2 ldg_relaxed2(const unsigned* p) {
    uint2 v; asm volatile("ld.relaxed.gpu.global.v2.u32 {%0,%1}, [%2];" : "=r"(v.x), "=r"(v.y) : "l"(p) : "memory"); return v;
}
__device__ __forceinline__ uint4 ldg_relaxed4(const unsigned* p) {
    uint4 v; asm volatile("ld.relaxed.gpu.global.v4.u32 {%0,%1,%2,%3}, [%4];"
                          : "=r"(v.x), "=r"(v.y), "=r"(v.z), "=r"(v.w) : "l"(p) : "memory"); return v;
}
__device__ __forceinline__ unsigned ldg_relaxed1(const unsigned* p) {
    unsigned v; asm volatile("ld.relaxed.gpu.global.u32 %0, [%1];" : "=r"(v) : "l"(p) : "memory"); return v;
}
__device__ __forceinline__ unsigned ldg_acquire1(const unsigned* p) {
    unsigned v; asm volatile("ld.acquire.gpu.global.u32 %0, [%1];" : "=r"(v) : "l"(p) : "memory"); return v;
}
__device__ __forceinline__ ulonglong2 ldg_relaxed64x2(const unsigned long long* p) {
    ulonglong2 v; asm volatile("ld.relaxed.gpu.global.v2.u64 {%0,%1}, [%2];" : "=l"(v.x), "=l"(v.y) : "l"(p) : "memory"); return v;
}
__device__ __forceinline__ void ldg_relaxed64x2_p(ulonglong2& v, const unsigned long long* p, bool pr) {
    asm volatile("{\n.reg .pred p;\nsetp.ne.u32 p, %3, 0;\n@p ld.relaxed.gpu.global.v2.u64 {%0,%1}, [%2];\n}\n"
                 : "+l"(v.x), "+l"(v.y) : "l"(p), "r"((unsigned)pr) : "memory");
}
__device__ __forceinline__ void stg_relaxed1(unsigned* p, unsigned v) {
    asm volatile("st.relaxed.gpu.global.u32 [%0], %1;" ::"l"(p), "r"(v) : "memory");
}
__device__ __forceinline__ void stg_relaxed4(unsigned* p, unsigned a, unsigned b, unsigned c, unsigned d) {
    asm volatile("st.relaxed.gpu.global.v4.u32 [%0], {%1,%2,%3,%4};" ::"l"(p), "r"(a), "r"(b), "r"(c), "r"(d) : "memory");
}
__device__ __forceinline__ unsigned long long tagged(float v, unsigned tag) {
    return ((unsigned long long)__float_as_uint(v) << 32) | tag;
}
__device__ __forceinline__ void stg_relaxed64x2(unsigned long long* p, unsigned long long a, unsigned long long b) {
    asm volatile("st.relaxed.gpu.global.v2.u64 [%0], {%1,%2};" ::"l"(p), "l"(a), "l"(b) : "memory");
}
__device__ __forceinline__ unsigned atom_add_lane0(unsigned* p, unsigned inc, int lane) {
    unsigned v = 0;
    asm volatile("{\n.reg .pred p;\nsetp.eq.s32 p, %3, 0;\n@p atom.relaxed.gpu.global.add.u32 %0, [%1], %2;\n}\n"
                 : "+r"(v) : "l"(p), "r"(inc), "r"(lane) : "memory");
    return v;
}
__device__ __forceinline__ float ex2(float x) { float y; asm("ex2.approx.ftz.f32 %0, %1;" : "=f"(y) : "f"(x)); return y; }
__device__ __forceinline__ float rcp(float x) { float y; asm("rcp.approx.ftz.f32 %0, %1;" : "=f"(y) : "f"(x)); return y; }

__device__ __forceinline__ float bfr(float x) { return __bfloat162float(__float2bfloat16_rn(x)); }
__device__ __forceinline__ unsigned bf_bits(float x) { return (unsigned)__bfloat16_as_ushort(__float2bfloat16_rn(x)); }
__device__ __forceinline__ float bf_hi(unsigned w) { return __uint_as_float(w & 0xffff0000u); }
__device__ __forceinline__ float bf_lo(unsigned w) { return __uint_as_float(w << 16); }
__device__ __forceinline__ unsigned pack_hi(unsigned lo_word, unsigned hi_word) {
    return __byte_perm(lo_word, hi_word, 0x7632);
}
__device__ __forceinline__ unsigned pack_bf2(float lo, float hi) {
    unsigned r; asm("cvt.rn.bf16x2.f32 %0, %1, %2;" : "=r"(r) : "f"(hi), "f"(lo)); return r;
}
__device__ __forceinline__ unsigned bf2_sub(unsigned a, unsigned b) { unsigned r; asm("sub.rn.bf16x2 %0, %1, %2;" : "=r"(r) : "r"(a), "r"(b)); return r; }
__device__ __forceinline__ unsigned bf2_mul(unsigned a, unsigned b) { unsigned r; asm("mul.rn.bf16x2 %0, %1, %2;" : "=r"(r) : "r"(a), "r"(b)); return r; }
__device__ __forceinline__ unsigned bf2_add(unsigned a, unsigned b) { unsigned r; asm("add.rn.bf16x2 %0, %1, %2;" : "=r"(r) : "r"(a), "r"(b)); return r; }
constexpr float LOG2E = 1.4426950408889634f;
constexpr float QSCALE = 0.08838834764831845f;
constexpr unsigned SPIN_LIMIT = 1u << 22;

template <int N>
__device__ __forceinline__ void fix_row16(const unsigned* base, int lane, unsigned tag16, uint2 (&v)[N]) {
    unsigned spins = 0;
    while (true) {
        bool ok = true;
#pragma unroll
        for (int i = 0; i < N; i++) {
            if ((v[i].x & 0xffffu) != tag16 || (v[i].y & 0xffffu) != tag16) {
                v[i] = ldg_relaxed2(base + 2 * (lane + 32 * i));
                ok = false;
            }
        }
        if (ok) break;
        if (++spins > SPIN_LIMIT) TRAP_AT(__LINE__);
    }
}
template <int N>
__device__ __forceinline__ void load_row16(const unsigned* base, int lane, uint2 (&v)[N]) {
#pragma unroll
    for (int i = 0; i < N; i++) v[i] = ldg_relaxed2(base + 2 * (lane + 32 * i));
}

__device__ __forceinline__ void ln_stats(const unsigned (&w)[9], unsigned& mean2, float& rsd) {
    const float sh = __shfl_sync(0xffffffffu, bf_lo(w[0]), 0);
    float s = 0.f, q = 0.f;
#pragma unroll
    for (int i = 0; i < 9; i++) {
        const float a = bf_lo(w[i]) - sh, b = bf_hi(w[i]) - sh;
        s += a + b;
        q = fmaf(a, a, q); q = fmaf(b, b, q);
    }
#pragma unroll
    for (int o = 16; o; o >>= 1) { s += __shfl_xor_sync(0xffffffffu, s, o); q += __shfl_xor_sync(0xffffffffu, q, o); }
    const float md = s * (1.0f / 576.0f);
    const float var = bfr(fmaxf(fmaf(-md, md, q * (1.0f / 576.0f)), 0.f));
    mean2 = pack_bf2(md + sh, md + sh);
    rsd = rcp(bfr(sqrtf(bfr(var + 1e-5f))));
}
__device__ __forceinline__ unsigned ln_apply(unsigned w, unsigned mean2, float rsd, unsigned c1, unsigned s) {
    const unsigned d = bf2_sub(w, mean2);
    const unsigned y = pack_bf2(bf_lo(d) * rsd, bf_hi(d) * rsd);
    return bf2_add(bf2_mul(y, c1), s);
}

__device__ __forceinline__ const unsigned* red_ptr(const unsigned* part, int cta, int warp, int lane) {
    return part + (size_t)(16 * warp + (lane >> 4)) * (DM * NB) + 64 * cta + 4 * (lane & 15);
}
__device__ __forceinline__ void red_issue(const unsigned* ptr, uint4 (&v)[8]) {
#pragma unroll
    for (int i = 0; i < 8; i++) v[i] = ldg_relaxed4(ptr + (size_t)(2 * i) * (DM * NB));
}
__device__ __forceinline__ float red_finish(const unsigned* ptr, uint4 (&v)[8], unsigned tag2, uint32_t sb, int tid, int twi) {
    const int warp = tid >> 5, lane = tid & 31;
    unsigned spins = 0;
    while (true) {
        bool ok = true;
#pragma unroll
        for (int i = 0; i < 8; i++) {
            if ((((v[i].x ^ tag2) | (v[i].y ^ tag2) | (v[i].z ^ tag2) | (v[i].w ^ tag2)) & 3u) != 0u) {
                v[i] = ldg_relaxed4(ptr + (size_t)(2 * i) * (DM * NB));
                ok = false;
            }
        }
        if (ok) break;
        if (++spins > SPIN_LIMIT) TRAP_AT(__LINE__);
    }
    __syncwarp();
    TW(twi);
    float f[4] = {0.f, 0.f, 0.f, 0.f};
#pragma unroll
    for (int i = 0; i < 8; i++) {
        f[0] += __uint_as_float(v[i].x); f[1] += __uint_as_float(v[i].y);
        f[2] += __uint_as_float(v[i].z); f[3] += __uint_as_float(v[i].w);
    }
#pragma unroll
    for (int e = 0; e < 4; e++) f[e] += __shfl_xor_sync(0xffffffffu, f[e], 16);
    if (lane < 16) sts128f(sb + SM_RED + (warp * 16 + lane) * 16, f[0], f[1], f[2], f[3]);
    cons_sync();
    float s = 0.f;
    if (tid < 64) {
        float r[8];
#pragma unroll
        for (int w = 0; w < 8; w++) r[w] = __uint_as_float(lds32(sb + SM_RED + (w * 64 + tid) * 4));
        s = ((r[0] + r[1]) + (r[2] + r[3])) + ((r[4] + r[5]) + (r[6] + r[7]));
    }
    return s;
}
__device__ __forceinline__ void put_partial(unsigned* dst, const float (&acc)[4], unsigned tag2) {
    stg_relaxed4(dst, (__float_as_uint(acc[0]) & ~3u) | tag2, (__float_as_uint(acc[1]) & ~3u) | tag2,
                 (__float_as_uint(acc[2]) & ~3u) | tag2, (__float_as_uint(acc[3]) & ~3u) | tag2);
}

__global__ void __launch_bounds__(NTHREADS, 1)
fused_kernel(const __grid_constant__ CUtensorMap tmK, const __grid_constant__ CUtensorMap tmV,
             const __grid_constant__ CUtensorMap tmQ,
             const __grid_constant__ CUtensorMap tmO, const __grid_constant__ CUtensorMap tmG,
             const __grid_constant__ CUtensorMap tmU, const __grid_constant__ CUtensorMap tmD,
             const Params prm) {
    extern __shared__ unsigned char smem_raw[];
    const uint32_t sb = (smem_u32(smem_raw) + 1023u) & ~1023u;
    unsigned char* sp = smem_raw + (sb - smem_u32(smem_raw));
    const int tid = threadIdx.x, lane = tid & 31, warp = tid >> 5;
    const int cta = blockIdx.x;
    const uint32_t bar_full = sb + SM_BAR, bar_empty = sb + SM_BAR + 64, bar_ctrl = sb + SM_BAR + 128;
    const uint32_t bar_wq = sb + SM_BAR + 160, bar_wo = bar_wq + 8, bar_gate = bar_wq + 32;
    volatile int2* meta = reinterpret_cast<volatile int2*>(sp + SM_META);
    volatile unsigned* s_epoch = reinterpret_cast<volatile unsigned*>(sp + SM_EPOCH);

    if (warp == 8) {
        if (lane == 0) {
            const unsigned e = ldg_relaxed1(&g_epoch);
            for (int i = 0; i < NTILE; i++) { mbar_init(bar_full + 8 * i, 1); mbar_init(bar_empty + 8 * i, 4); }
            for (int i = 0; i < 11; i++) mbar_init(bar_ctrl + 8 * i, 1);
            asm volatile("fence.mbarrier_init.release.cluster;" ::: "memory");
            asm volatile("fence.proxy.async.shared::cta;" ::: "memory");
            prefetch_map(&tmQ); prefetch_map(&tmK); prefetch_map(&tmV);
            if (WQD == 2) { const long long t0 = clock64(); while (clock64() - t0 < NCD) { } }
            if (WQD != 1) {
                if (cta < NROLE) {
                    mbar_expect_tx(bar_wq, 36864);
                    for (int i = 0; i < 3; i++) tma2d(sb + SM_WB + i * 12288, &tmQ, 32 * cta, 192 * i, bar_wq);
                } else {
                    mbar_arrive(bar_wq);
                }
            }
            *s_epoch = e;
        }
        TSG(24, 256);
        __syncthreads();
        if (WQD == 1 && lane == 0) {
            if (cta < NROLE) {
                mbar_expect_tx(bar_wq, 36864);
                for (int i = 0; i < 3; i++) tma2d(sb + SM_WB + i * 12288, &tmQ, 32 * cta, 192 * i, bar_wq);
            } else {
                mbar_arrive(bar_wq);
            }
        }
        const unsigned epoch = *s_epoch;
        const int par = epoch & 1;
        unsigned* ctr = &g_tk[par][0];
        uint64_t pol;
        asm volatile("createpolicy.fractional.L2::evict_first.b64 %0, 1.0;" : "=l"(pol));
        const unsigned nst = U0 * gridDim.x;
        unsigned pend = 0;
        int stage = 0;
        auto wchunk = [&](int i) {
            if (i < 3) {
                mbar_expect_tx(bar_wo + 8 * i, 12288);
                const int r0 = (cta >> 3) * 256 + (cta & 7) * 16;
                for (int r = 0; r < 6; r++) {
                    const int b = 6 * i + r;
                    const int rg = b >= 9, cb = b - 9 * rg;
                    tma2d(sb + SM_WREG + b * 2048, &tmO, 64 * cb, r0 + 128 * rg, bar_wo + 8 * i);
                }
            } else {
                mbar_expect_tx(bar_gate + 8 * (i - 3), 15360);
                tma2d(sb + SM_WB + (i - 3) * 15360, &tmG, (36 * cta) & ~7, 192 * (i - 3), bar_gate + 8 * (i - 3));
            }
        };
        auto advance = [&](bool block) {
            if (stage == 0) {
                if (cta < NROLE) {
                    unsigned* a = g_wop + (size_t)cta * (DM * NB);
                    unsigned* b = g_dnp + (size_t)cta * (DM * NB);
                    for (int i = lane; i < DM * NB / 4; i += 32) { stg_relaxed4(a + 4 * i, 0u, 0u, 0u, 0u); stg_relaxed4(b + 4 * i, 0u, 0u, 0u, 0u); }
                    if (cta < NRED) {
                        const int wcol = 8 * (cta >> 1) + 2 * (cta & 1) + 4 * ((lane >> 1) & 1) + (lane & 1);
                        stg_relaxed1(&g_x2[(lane >> 2) * (DM / 2) + wcol], 0u);
                    }
                }
                __syncwarp();
            } else if (stage == 1) {
                if (lane == 0) {
                    asm volatile("fence.acq_rel.gpu;" ::: "memory");
                    atomicAdd(&g_started[par], 1u);
                }
            } else if (stage == 2) {
                unsigned seen = 0;
                if (lane == 0) {
                    unsigned spins = 0;
                    while ((seen = ldg_acquire1(&g_started[par])) < gridDim.x && block) { if (++spins > SPIN_LIMIT) TRAP_AT(__LINE__); __nanosleep(100); }
                }
                if (__shfl_sync(0xffffffffu, seen, 0) < gridDim.x) return;
                if (lane == 0) {
                    if (cta == 0) {
                        g_started[par ^ 1] = 0;
                        g_epoch = epoch + 1;
                    }
                }
                __syncwarp();
                if (cta == 0 && lane == 0) stg_relaxed1(&g_tk[par ^ 1][0], 0u);
            }
            stage++;
        };
        int n = 0;
        for (;; n++) {
            const unsigned tk = (n < U0) ? (unsigned)n * gridDim.x + (unsigned)cta : __shfl_sync(0xffffffffu, pend, 0) + nst;
            if (tk >= (unsigned)(NPAIR * UNITS)) break;
            if (n >= U0 - 1) pend = atom_add_lane0(ctr, 1u, lane);
            const int iK = 2 * n;
            const int sK = iK & 7;
            const uint32_t eph = ((iK >> 3) & 1) ^ 1;
            mbar_wait(bar_empty + 8 * sK, eph);
            const int row = (int)tk * (UKEYS * 2);
            if (lane == 0) {
                meta[n & 3].x = (int)tk;
                mbar_arrive(bar_ctrl + 8 * (n & 3));
            }
            const int infl = (iK < NRAMP) ? INFL0 : INFL;
            if (KVGATE == 2 && iK == 0) mbar_wait(bar_wq, 0);
            if (KVGATE == 1 && iK == 2) mbar_wait(bar_wq, 0);
            if (iK >= infl) mbar_wait(bar_full + 8 * ((iK - infl) & 7), ((iK - infl) >> 3) & 1);
            if (lane == 0) {
                mbar_expect_tx(bar_full + 8 * sK, n >= U0 ? TILE + 1024 : TILE);
                tma2d_s(sb + SM_RING + sK * TILE, &tmK, 0, row, bar_full + 8 * sK, pol);
                if (n >= U0)
                    asm volatile("cp.async.bulk.shared::cluster.global.mbarrier::complete_tx::bytes [%0], [%1], 1024, [%2];"
                                 ::"r"(sb + SM_BUFA + (n & 3) * 1024), "l"(g_q + (tk >> 7) * 256), "r"(bar_full + 8 * sK) : "memory");
            }
            mbar_wait(bar_empty + 8 * (sK + 1), eph);
            if (iK + 1 >= infl) mbar_wait(bar_full + 8 * ((iK + 1 - infl) & 7), ((iK + 1 - infl) >> 3) & 1);
            if (lane == 0) {
                mbar_expect_tx(bar_full + 8 * (sK + 1), TILE);
                tma2d_s(sb + SM_RING + (sK + 1) * TILE, &tmV, 0, row, bar_full + 8 * (sK + 1), pol);
                if (cta < NROLE && n >= WSTART && n < WSTART + WEARLY) wchunk(n - WSTART);
            }
            __syncwarp();
            if ((stage == 0 && n >= NCLR) || (stage == 1 && n >= NCLR + 4) || (stage == 2 && n >= NCLR + 24 && (n & 7) == 0)) advance(false);
        }
        TSP(13);
        while (stage < 3) advance(true);
        if (lane == 0) {
            for (int e = 0; e < 2; e++) {
                const int ne = n + e;
                mbar_wait(bar_empty + 8 * ((2 * ne) & 7), (((2 * ne) >> 3) & 1) ^ 1);
                meta[ne & 3].x = -1 - n;
                mbar_arrive(bar_ctrl + 8 * (ne & 3));
            }
            if (cta < NROLE) {
                const int gc = (36 * cta) & ~7;
                const int early = min(max(0, n - WSTART), WEARLY);
                uint32_t hb[TINFL], hp[TINFL];
#pragma unroll
                for (int i = 0; i < TINFL; i++) {
                    const int it = 2 * n - TINFL + i;
                    hb[i] = bar_full + 8 * (it & 7); hp[i] = (it >> 3) & 1;
                }
#pragma unroll 1
                for (int i = 0; i < 12; i++) {
                    int kind, j;
                    if (i < 3) { kind = 0; j = i; }
                    else if (i < 9) { kind = (i - 3) & 1; j = kind ? ((i - 3) >> 1) : 3 + ((i - 3) >> 1); }
                    else { kind = 1; j = i - 6; }
                    if (kind == 0 && j < early) continue;
                    mbar_wait(hb[0], hp[0]);
#pragma unroll
                    for (int k = 0; k + 1 < TINFL; k++) { hb[k] = hb[k + 1]; hp[k] = hp[k + 1]; }
                    if (kind == 0) {
                        wchunk(j);
                        hb[TINFL - 1] = (j < 3) ? bar_wo + 8 * j : bar_gate + 8 * (j - 3); hp[TINFL - 1] = 0;
                    } else {
                        const int it = 2 * n + j;
                        const int s = it & 7;
                        const uint32_t dst = sb + SM_RING + s * TILE;
                        const uint32_t fb = bar_full + 8 * s;
                        mbar_wait(bar_empty + 8 * s, ((it >> 3) & 1) ^ 1);
                        if (j < 3) {
                            mbar_expect_tx(fb, 15360);
                            tma2d(dst, &tmU, gc, 192 * j, fb);
                        } else {
                            mbar_expect_tx(fb, 3 * 4608);
                            for (int r = 0; r < 3; r++) tma2d(dst + r * 5120, &tmD, 64 * (3 * (j - 3) + r), 36 * cta, fb);
                        }
                        hb[TINFL - 1] = fb; hp[TINFL - 1] = (it >> 3) & 1;
                    }
                }
            }
        }
        TSG(26, 256);
        return;
    }

    const int g = lane >> 2, t = lane & 3;
    TS(0);
    TW(0);
    const uint32_t bufA = sb + SM_BUFA;
    const uint32_t bA = bufA + (g * BUFA_PITCH + 2 * t) * 2;
    const int kr = (lane & 7) + 8 * (lane >> 4), cs = (lane >> 3) & 1;
    constexpr int SM_RED2 = SM_WREG + 73728;
    const bool crit = cta < NRED;
    const int c00 = crit ? 8 * cta : 1152 + 32 * (cta - NRED);
    const int c01 = crit ? DM + 8 * cta : c00 + 8;
    const int c1 = crit ? (cta < 32 ? 1152 + 16 * (112 + cta) : -1) : c00 + 16;
    float x0 = 0.f, x1 = 0.f;
    if (cta < NROLE) {
        const unsigned* cw = reinterpret_cast<const unsigned*>(prm.c) + warp * 288;
        unsigned cv[9], xw[9];
#pragma unroll
        for (int i = 0; i < 9; i++) cv[i] = __ldg(cw + lane + 32 * i);
        if (crit) {
#pragma unroll
            for (int i = 0; i < 9; i++) xw[i] = __ldg(reinterpret_cast<const unsigned*>(prm.x) + warp * 288 + lane + 32 * i);
            if (warp == 0) {
                x0 = __bfloat162float(prm.x[(2 * t) * DM + 8 * cta + g]);
                x1 = __bfloat162float(prm.x[(2 * t + 1) * DM + 8 * cta + g]);
            }
#pragma unroll
            for (int i = 0; i < 5; i++) {
                const int q = tid + 256 * i;
                const int r = q >> 1, ch = q & 1;
                if (q < 1152) cp_async16(sb + SM_WREG + r * 32 + ((ch ^ ((r >> 2) & 1)) << 4), prm.wmod + (size_t)r * 3456 + (ch ? c01 : c00));
            }
        }
        asm volatile("cp.async.commit_group;" ::: "memory");
        if (warp == 1) {
#pragma unroll
            for (int i = 0; i < 2; i++) stg_relaxed4(&g_q[(4 * i + g / 2) * 4096 + 32 * cta + 4 * (lane & 7)], 0u, 0u, 0u, 0u);
        } else if (warp == 2) {
            if (crit && lane < 16) stg_relaxed4(&g_h[(lane >> 1) * DM + 8 * cta + 4 * (lane & 1)], 0u, 0u, 0u, 0u);
            for (int i = lane; i < 48; i += 32) sts32(sb + SM_ACT + ((i / 6) * ACT_PITCH + 36 + 2 * (i % 6)) * 2, 0u);
        }
#pragma unroll
        for (int i = 0; i < 9; i++) {
            const float a = bf_lo(cv[i]), b = bf_hi(cv[i]);
            sts32(bufA + (warp * BUFA_PITCH + 2 * (lane + 32 * i)) * 2,
                  pack_bf2(a * rcp(1.0f + ex2(-a * LOG2E)), b * rcp(1.0f + ex2(-b * LOG2E))));
        }
        if (crit) {
            unsigned mean2; float rsd;
            ln_stats(xw, mean2, rsd);
            if (lane == 0) sts64f(sb + SM_STAT + 8 * warp, bf_lo(mean2), rsd);
        }
        if (!crit) {
#pragma unroll
            for (int i = 0; i < 9; i++) {
                const int q = tid + 256 * i;
                const int r = q >> 2, ch = q & 1, tl = (q >> 1) & 1;
                cp_async16(sb + SM_WREG + tl * 18432 + r * 32 + ((ch ^ ((r >> 2) & 1)) << 4), prm.wmod + (size_t)r * 3456 + c00 + 8 * (q & 3));
            }
        } else if (c1 >= 0) {
#pragma unroll
            for (int i = 0; i < 5; i++) {
                const int q = tid + 256 * i;
                const int r = q >> 1, ch = q & 1;
                if (q < 1152) cp_async16(sb + SM_WREG + 18432 + r * 32 + ((ch ^ ((r >> 2) & 1)) << 4), prm.wmod + (size_t)r * 3456 + c1 + 8 * ch);
            }
        }
        asm volatile("cp.async.commit_group;" ::: "memory");
        asm volatile("cp.async.wait_group 1;" ::: "memory");
    }
    __syncthreads();
    const unsigned epoch = *s_epoch;
    TW(1);
    const int par = epoch & 1;
    const unsigned tag16 = epoch % 65535u + 1u;
    const unsigned tag2 = epoch % 3u + 1u;

    if (cta < NROLE) {
        uint32_t mb[5][2];
#pragma unroll
        for (int i = 0; i < 5; i++) {
            mb[i][0] = mb[i][1] = 0u;
            if (i < 4 || warp < 4) { mb[i][0] = lds32(bA + (warp + 8 * i) * 32); mb[i][1] = lds32(bA + (warp + 8 * i) * 32 + 16); }
        }
        auto mod_mma = [&](uint32_t tb, uint32_t red) {
            float acc[4] = {0.f, 0.f, 0.f, 0.f};
            const uint32_t ab = tb + kr * 32 + ((cs ^ ((kr >> 2) & 1)) << 4) + warp * 512;
            uint32_t a[5][4];
#pragma unroll
            for (int i = 0; i < 5; i++)
                if (i < 4 || warp < 4) ldsm4t(ab + i * 4096, a[i]);
#pragma unroll
            for (int i = 0; i < 5; i++)
                if (i < 4 || warp < 4) mma16816(acc, a[i], mb[i][0], mb[i][1]);
            sts128f(red + tid * 16, acc[0], acc[1], acc[2], acc[3]);
        };
        auto mod_sum = [&](uint32_t red) {
            float4 u[8];
#pragma unroll
            for (int k = 0; k < 8; k++) u[k] = lds128f(red + (k * 32 + lane) * 16);
            float4 v;
            v.x = ((u[0].x + u[1].x) + (u[2].x + u[3].x)) + ((u[4].x + u[5].x) + (u[6].x + u[7].x));
            v.y = ((u[0].y + u[1].y) + (u[2].y + u[3].y)) + ((u[4].y + u[5].y) + (u[6].y + u[7].y));
            v.z = ((u[0].z + u[1].z) + (u[2].z + u[3].z)) + ((u[4].z + u[5].z) + (u[6].z + u[7].z));
            v.w = ((u[0].w + u[1].w) + (u[2].w + u[3].w)) + ((u[4].w + u[5].w) + (u[6].w + u[7].w));
            return v;
        };
        auto mod_put = [&](const float4 v, int col) {
            stg_relaxed1(&g_mod[(2 * t) * 3456 + col + g], (bf_bits(v.x) << 16) | tag16);
            stg_relaxed1(&g_mod[(2 * t + 1) * 3456 + col + g], (bf_bits(v.y) << 16) | tag16);
            stg_relaxed1(&g_mod[(2 * t) * 3456 + col + 8 + g], (bf_bits(v.z) << 16) | tag16);
            stg_relaxed1(&g_mod[(2 * t + 1) * 3456 + col + 8 + g], (bf_bits(v.w) << 16) | tag16);
        };
        if (crit) mod_mma(sb + SM_WREG, sb + SM_RED);
        cons_sync();
        if (crit && warp == 0) {
            const float4 v = mod_sum(sb + SM_RED);
            const float4 st = lds128f(sb + SM_STAT + 16 * t);
            const float y0 = bfr(bfr(x0 - st.x) * st.y), y1 = bfr(bfr(x1 - st.z) * st.w);
            const float h0 = bfr(y0 * bfr(1.0f + bfr(v.z))) + bfr(v.x);
            const float h1 = bfr(y1 * bfr(1.0f + bfr(v.w))) + bfr(v.y);
            stg_relaxed1(&g_h[(2 * t) * DM + 8 * cta + g], (bf_bits(h0) << 16) | tag16);
            stg_relaxed1(&g_h[(2 * t + 1) * DM + 8 * cta + g], (bf_bits(h1) << 16) | tag16);
        }
        TS(1);
        TW(2);
        mbar_wait(bar_wq, 0);
        const int tile = warp & 1, kq = warp >> 1;
        uint32_t aq[9][4];
        {
            const uint32_t ab = sb + SM_WB + (144 * kq + kr) * 64 + (((2 * tile + cs) ^ ((kr >> 1) & 3)) << 4);
#pragma unroll
            for (int i = 0; i < 9; i++) ldsm4t(ab + i * 1024, aq[i]);
        }
        TW(3);
        uint2 hv[9];
        load_row16<9>(g_h + warp * DM, lane, hv);
        fix_row16<9>(g_h + warp * DM, lane, tag16, hv);
        __syncwarp();
        TW(4);
#pragma unroll
        for (int i = 0; i < 9; i++) sts32(bufA + (warp * BUFA_PITCH + 2 * (lane + 32 * i)) * 2, pack_hi(hv[i].x, hv[i].y));
        cons_sync();
        float acc0[4] = {0.f, 0.f, 0.f, 0.f}, acc1[4] = {0.f, 0.f, 0.f, 0.f};
#pragma unroll
        for (int i = 0; i < 9; i++) {
            const uint32_t b0 = lds32(bA + (9 * kq + i) * 32), b1 = lds32(bA + (9 * kq + i) * 32 + 16);
            if (i & 1) mma16816(acc1, aq[i], b0, b1); else mma16816(acc0, aq[i], b0, b1);
        }
        sts128f(sb + SM_RED + tid * 16, acc0[0] + acc1[0], acc0[1] + acc1[1], acc0[2] + acc1[2], acc0[3] + acc1[3]);
        asm volatile("fence.proxy.async.shared::cta;" ::: "memory");
        cons_sync();
        if (warp < 2) {
            float4 v = lds128f(sb + SM_RED + (warp * 32 + lane) * 16);
#pragma unroll
            for (int k = 1; k < 4; k++) { const float4 u = lds128f(sb + SM_RED + ((warp + 2 * k) * 32 + lane) * 16); v.x += u.x; v.y += u.y; v.z += u.z; v.w += u.w; }
            const int col = 32 * cta + 16 * warp + g;
            stg_relaxed1(&g_q[(2 * t) * 4096 + col], (bf_bits(v.x) << 16) | tag16);
            stg_relaxed1(&g_q[(2 * t + 1) * 4096 + col], (bf_bits(v.y) << 16) | tag16);
            stg_relaxed1(&g_q[(2 * t) * 4096 + col + 8], (bf_bits(v.z) << 16) | tag16);
            stg_relaxed1(&g_q[(2 * t + 1) * 4096 + col + 8], (bf_bits(v.w) << 16) | tag16);
        }
        TW(13);
        if (c1 >= 0) {
            asm volatile("cp.async.wait_group 0;" ::: "memory");
            cons_sync();
            if (!crit) mod_mma(sb + SM_WREG, sb + SM_RED2 + 4096);
            mod_mma(sb + SM_WREG + 18432, sb + SM_RED2);
            asm volatile("fence.proxy.async.shared::cta;" ::: "memory");
            cons_sync();
            if (warp == 2) mod_put(mod_sum(sb + SM_RED2), c1);
            if (warp == 3 && !crit) mod_put(mod_sum(sb + SM_RED2 + 4096), c00);
        }
    }
    TS(2);
    TW(5);
    unsigned cpk[9], spk[9];
    const int ocol = 16 * (cta >> 1) + 4 * (cta & 1) + ((tid >> 4) & 3) + 8 * ((tid >> 1) & 1);
    const int ob = 2 * ((tid >> 2) & 3) + (tid & 1);
    const bool oth = cta < NRED && tid < 64;
    unsigned gab = 0; float xin = 0.f;
#pragma unroll
    for (int i = 0; i < 9; i++) { cpk[i] = 0; spk[i] = 0; }

    const int grp = warp >> 2, wq = warp & 3;
    int n = grp;
    int nend = 0;
    int jb = (cta < NROLE) ? grp : NB;
    const int hk = (cta >> 3) & 15;
    const unsigned tagF = epoch % 0xfffffffeu + 1u;
    auto job = [&](auto hook) {
        const unsigned tg = (epoch * 8u + (unsigned)jb) % 0xfffffffeu + 1u;
        const int half = lane >> 4;
        const unsigned long long* rec = g_part + (size_t)(hk * UNITS + 32 * wq) * RSTRIDE;
        const unsigned long long* pd = rec + half * RSTRIDE + 2 * ((cta & 7) * 16 + (lane & 15));
        const unsigned long long* ph2 = rec + (lane >> 1) * RSTRIDE + 256 + 2 * (lane & 1);
        ulonglong2 w[16], hd[2];
#pragma unroll
        for (int i = 0; i < 16; i++) w[i] = make_ulonglong2(0ull, 0ull);
        hd[0] = hd[1] = make_ulonglong2(0ull, 0ull);
        unsigned got = 0, spins = 0;
        while (true) {
            ldg_relaxed64x2_p(hd[0], ph2, !((got >> 16) & 1u));
            ldg_relaxed64x2_p(hd[1], ph2 + 16 * RSTRIDE, !((got >> 17) & 1u));
#pragma unroll
            for (int i = 0; i < 16; i++) ldg_relaxed64x2_p(w[i], pd + 2 * i * RSTRIDE, !((got >> i) & 1u));
            hook();
#pragma unroll
            for (int i = 0; i < 2; i++)
                if ((unsigned)hd[i].x == tg && (unsigned)hd[i].y == tg) got |= 1u << (16 + i);
#pragma unroll
            for (int i = 0; i < 16; i++)
                if ((unsigned)w[i].x == tg && (unsigned)w[i].y == tg) got |= 1u << i;
            if (__all_sync(0xffffffffu, got == 0x3ffffu)) break;
            if (++spins > SPIN_LIMIT) TRAP_AT(__LINE__);
        }
        TW(11);
        const float m0 = __uint_as_float((unsigned)(hd[0].x >> 32)), m1 = __uint_as_float((unsigned)(hd[1].x >> 32));
        float M = fmaxf(m0, m1);
#pragma unroll
        for (int of = 2; of <= 16; of <<= 1) M = fmaxf(M, __shfl_xor_sync(0xffffffffu, M, of));
        const float f0 = ex2((m0 - M) * LOG2E), f1 = ex2((m1 - M) * LOG2E);
        const uint32_t fs = sb + SM_RED + warp * 256;
        const uint32_t fo = fs + ((((lane >> 1) & 1) * 32 + (lane >> 2) * 2 + (lane & 1)) << 2);
        sts32(fo, __float_as_uint(f0));
        sts32(fo + 64, __float_as_uint(f1));
        float L = f0 * __uint_as_float((unsigned)(hd[0].y >> 32)) + f1 * __uint_as_float((unsigned)(hd[1].y >> 32));
        __syncwarp();
#pragma unroll
        for (int of = 2; of <= 16; of <<= 1) L += __shfl_xor_sync(0xffffffffu, L, of);
        float a0 = 0.f, a1 = 0.f;
#pragma unroll
        for (int k = 0; k < 8; k++) {
            const float4 ff = lds128f(fs + half * 128 + k * 16);
            a0 = fmaf(ff.x, __uint_as_float((unsigned)(w[2 * k].x >> 32)), a0);
            a1 = fmaf(ff.y, __uint_as_float((unsigned)(w[2 * k].y >> 32)), a1);
            a0 = fmaf(ff.z, __uint_as_float((unsigned)(w[2 * k + 1].x >> 32)), a0);
            a1 = fmaf(ff.w, __uint_as_float((unsigned)(w[2 * k + 1].y >> 32)), a1);
        }
        const float v = (half ? a1 : a0) + __shfl_xor_sync(0xffffffffu, half ? a0 : a1, 16);
        const int alt = grp * 2 + ((jb >> 1) & 1);
        const uint32_t pv = sb + SM_RED + 2048 + alt * 512, pm = sb + SM_SC + 1024 + alt * 64;
        sts32(pv + wq * 128 + lane * 4, __float_as_uint(v));
        if (lane < 2) sts64f(pm + wq * 16 + lane * 8, M, L);
        group_sync(grp);
        if (wq == 0) {
            float mw[4], lw[4], vw[4];
#pragma unroll
            for (int k = 0; k < 4; k++) {
                const float4 q4 = lds128f(pm + k * 16);
                mw[k] = half ? q4.z : q4.x; lw[k] = half ? q4.w : q4.y;
                vw[k] = __uint_as_float(lds32(pv + k * 128 + lane * 4));
            }
            const float Mx = fmaxf(fmaxf(mw[0], mw[1]), fmaxf(mw[2], mw[3]));
            float num = 0.f, den = 0.f;
#pragma unroll
            for (int k = 0; k < 4; k++) { const float f = ex2((mw[k] - Mx) * LOG2E); num = fmaf(f, vw[k], num); den = fmaf(f, lw[k], den); }
            sts16(sb + SM_ACT + (jb * ACT_PITCH + lane) * 2, bf_bits(__fdividef(num, den)));
            } else if (wq == 1 && lane == 0 && jb < NB - 1) {
                asm volatile("st.release.gpu.global.u32 [%0], %1;" ::"l"(&g_cf[(16 * jb + hk) * 8 + (cta & 7)]), "r"(tagF) : "memory");
        }
        jb += 2;
    };
    {
        uint32_t kpre[2], vpre[2];
        {
            const int key = (lane & 7) + 8 * ((lane >> 3) & 1), kc = lane >> 4;
#pragma unroll
            for (int h = 0; h < 2; h++) {
                const int r = 2 * (16 * wq + key) + h;
                kpre[h] = r * 128 + ((kc ^ (r & 7)) << 4);
            }
            const int k7 = (lane & 7), hi = lane >> 4, cv = (lane >> 3) & 1;
            const int vkey = (k7 >> 1) + 8 * (k7 & 1) + 4 * hi;
            const int r = 2 * vkey + (wq >> 1);
#pragma unroll
            for (int i = 0; i < 2; i++) vpre[i] = (r * 128 + ((cv ^ (r & 7)) << 4)) ^ (((2 * wq + i) & 3) << 5);
        }
        bool mod_done = cta >= NROLE;
        for (;; n += 2) {
            const uint32_t ph = (n >> 2) & 1;
            mbar_wait(bar_ctrl + 8 * (n & 3), ph);
            const int tk = meta[n & 3].x, np = tk >> 7;
            if ((n >> 1) == DBGN) TW(23);
            if (!mod_done && (n >= NMOD || tk < 0)) {
                mod_done = true;
                uint2 cbv[9], sbv[9];
                load_row16<9>(g_mod + warp * 3456 + 4 * DM, lane, cbv);
                load_row16<9>(g_mod + warp * 3456 + 3 * DM, lane, sbv);
                if (oth) {
                    unsigned gaw, gbw, spins = 0;
                    xin = __bfloat162float(prm.x[ob * DM + ocol]);
                    do {
                        gaw = ldg_relaxed1(&g_mod[ob * 3456 + 2 * DM + ocol]);
                        gbw = ldg_relaxed1(&g_mod[ob * 3456 + 5 * DM + ocol]);
                        if (++spins > SPIN_LIMIT) TRAP_AT(__LINE__);
                    } while ((gaw & 0xffffu) != tag16 || (gbw & 0xffffu) != tag16);
                    gab = pack_hi(gaw, gbw);
                }
                fix_row16<9>(g_mod + warp * 3456 + 4 * DM, lane, tag16, cbv);
                fix_row16<9>(g_mod + warp * 3456 + 3 * DM, lane, tag16, sbv);
#pragma unroll
                for (int i = 0; i < 9; i++) {
                    cpk[i] = pack_bf2(1.0f + bf_hi(cbv[i].x), 1.0f + bf_hi(cbv[i].y));
                    spk[i] = pack_hi(sbv[i].x, sbv[i].y);
                }
            }
            if (tk < 0) { nend = -1 - tk; break; }
            while (jb < NB && np >= 16 * jb + hk + JD) job([] {});
            uint32_t qf[8][2];
            unsigned fl = tagF;
            if (np >= 16 && lane < 8) fl = ldg_relaxed1(&g_cf[(np - 16) * 8 + lane]);
            const int sK = (2 * n) & 7;
            const uint32_t kb = sb + SM_RING + sK * TILE, vb = kb + TILE;
            {
                uint2 qa[8], qb2[8];
                const uint32_t qs0 = sb + SM_BUFA + (n & 3) * 1024, qs = qs0 + ((g & 1) * 128 + 2 * t) * 4;
                bool ok = false;
                if (n >= U0) {
                    mbar_wait(bar_full + 8 * sK, ph);
                    ok = true;
#pragma unroll
                    for (int ks = 0; ks < 8; ks++) {
                        qa[ks] = lds64u(qs + 64 * ks); qb2[ks] = lds64u(qs + 64 * ks + 32);
                        ok = ok && ((qa[ks].x & 0xffffu) == tag16) && ((qa[ks].y & 0xffffu) == tag16) &&
                             ((qb2[ks].x & 0xffffu) == tag16) && ((qb2[ks].y & 0xffffu) == tag16);
                    }
                    ok = __all_sync(0xffffffffu, ok);
                }
                if (!ok) {
                    if (n >= U0) group_sync(grp);
                    const unsigned* qb = g_q + np * 256 + 4 * lane;
                    unsigned spins = 0;
                    uint4 x0, x1;
                    while (true) {
                        x0 = ldg_relaxed4(qb); x1 = ldg_relaxed4(qb + 128);
                        const unsigned e = ((x0.x ^ tag16) | (x0.y ^ tag16) | (x0.z ^ tag16) | (x0.w ^ tag16) |
                                            (x1.x ^ tag16) | (x1.y ^ tag16) | (x1.z ^ tag16) | (x1.w ^ tag16)) & 0xffffu;
                        if (__all_sync(0xffffffffu, e == 0u)) break;
                        if (++spins > SPIN_LIMIT) TRAP_AT(__LINE__);
                    }
                    sts128f(qs0 + 16 * lane, __uint_as_float(x0.x), __uint_as_float(x0.y), __uint_as_float(x0.z), __uint_as_float(x0.w));
                    sts128f(qs0 + 512 + 16 * lane, __uint_as_float(x1.x), __uint_as_float(x1.y), __uint_as_float(x1.z), __uint_as_float(x1.w));
                    asm volatile("fence.proxy.async.shared::cta;" ::: "memory");
                    __syncwarp();
#pragma unroll
                    for (int ks = 0; ks < 8; ks++) { qa[ks] = lds64u(qs + 64 * ks); qb2[ks] = lds64u(qs + 64 * ks + 32); }
                }
#pragma unroll
                for (int ks = 0; ks < 8; ks++) { qf[ks][0] = pack_hi(qa[ks].x, qa[ks].y); qf[ks][1] = pack_hi(qb2[ks].x, qb2[ks].y); }
            }
            if ((n >> 1) == DBGN) TW(27);
            if (n == 0) TS(3);
            if (n < 2) TW(6);
            if (n == 4 || n == 5) TW(7);
            if (n == 4) TS(4);
            mbar_wait(bar_full + 8 * sK, ph);
            if ((n >> 1) == DBGN) TW(28);
            float c0[4] = {0.f, 0.f, 0.f, 0.f}, c1a[4] = {0.f, 0.f, 0.f, 0.f};
#pragma unroll
            for (int ks = 0; ks < 8; ks += 2) {
                uint32_t a[4], b[4];
                ldsm4(kb + (kpre[ks >> 2] ^ ((ks & 3) << 5)), a);
                ldsm4(kb + (kpre[(ks + 1) >> 2] ^ (((ks + 1) & 3) << 5)), b);
                mma16816(c0, a, qf[ks][0], qf[ks][1]);
                mma16816(c1a, b, qf[ks + 1][0], qf[ks + 1][1]);
            }
            __syncwarp();
            if (lane == 0) mbar_arrive(bar_empty + 8 * sK);
            float s0 = (t & 1) ? (c0[1] + c1a[1]) : (c0[0] + c1a[0]);
            float s1 = (t & 1) ? (c0[3] + c1a[3]) : (c0[2] + c1a[2]);
            s0 = bfr(bfr(s0) * QSCALE);
            s1 = bfr(bfr(s1) * QSCALE);
            const uint32_t ssc = sb + SM_SC + grp * 512 + ((n >> 1) & 1) * 256;
            if (t < 2) sts32(ssc + (((t * 4 + (g & 3)) * 8 + wq * 2 + (g >> 2)) << 2), pack_hi(__float_as_uint(s0), __float_as_uint(s1)));
            group_sync(grp);
            if ((n >> 1) == DBGN) TW(29);
            uint32_t pb[8];
            {
                const float4 x0 = lds128f(ssc + ((g & 1) * 4 + t) * 32), x1 = lds128f(ssc + ((g & 1) * 4 + t) * 32 + 16);
                pb[0] = __float_as_uint(x0.x); pb[1] = __float_as_uint(x0.y); pb[2] = __float_as_uint(x0.z); pb[3] = __float_as_uint(x0.w);
                pb[4] = __float_as_uint(x1.x); pb[5] = __float_as_uint(x1.y); pb[6] = __float_as_uint(x1.z); pb[7] = __float_as_uint(x1.w);
            }
            float M = -INFINITY, L = 0.f;
#pragma unroll
            for (int i = 0; i < 8; i++) M = fmaxf(M, fmaxf(bf_lo(pb[i]), bf_hi(pb[i])));
            M = fmaxf(M, __shfl_xor_sync(0xffffffffu, M, 1));
            M = fmaxf(M, __shfl_xor_sync(0xffffffffu, M, 2));
#pragma unroll
            for (int i = 0; i < 8; i++) {
                const float p0 = ex2((bf_lo(pb[i]) - M) * LOG2E), p1 = ex2((bf_hi(pb[i]) - M) * LOG2E);
                L += p0 + p1;
                pb[i] = pack_bf2(p0, p1);
            }
            L += __shfl_xor_sync(0xffffffffu, L, 1);
            L += __shfl_xor_sync(0xffffffffu, L, 2);
            float o[2][4] = {{0.f, 0.f, 0.f, 0.f}, {0.f, 0.f, 0.f, 0.f}};
            mbar_wait(bar_full + 8 * (sK + 1), ph);
            if ((n >> 1) == DBGN) TW(30);
#pragma unroll
            for (int ks = 0; ks < 4; ks++) {
                uint32_t a[4], b[4];
                ldsm4t(vb + vpre[0] + ks * 4096, a);
                ldsm4t(vb + vpre[1] + ks * 4096, b);
                mma16816(o[0], a, pb[2 * ks], pb[2 * ks + 1]);
                mma16816(o[1], b, pb[2 * ks], pb[2 * ks + 1]);
            }
            __syncwarp();
            if (lane == 0) mbar_arrive(bar_empty + 8 * (sK + 1));
            {
                unsigned spins = 0;
                while (!__all_sync(0xffffffffu, fl == tagF)) {
                    if (++spins > SPIN_LIMIT) TRAP_AT(__LINE__);
                    if (lane < 8) fl = ldg_relaxed1(&g_cf[(np - 16) * 8 + lane]);
                }
            }
            {
                const unsigned tg = (epoch * 8u + (unsigned)(np >> 4)) % 0xfffffffeu + 1u;
                unsigned long long* rec = g_part + (size_t)(tk & (16 * UNITS - 1)) * RSTRIDE;
                const float u0 = (t & 2) ? o[1][0] : o[0][0], u1 = (t & 2) ? o[1][1] : o[0][1];
                const float u2 = (t & 2) ? o[1][2] : o[0][2], u3 = (t & 2) ? o[1][3] : o[0][3];
                const int d = 32 * wq + 8 * t + g;
                stg_relaxed64x2(rec + 2 * d, tagged((t & 1) ? u2 : u0, tg), tagged((t & 1) ? u3 : u1, tg));
                if (wq == 0 && t == 0 && g < 2) stg_relaxed64x2(rec + 256 + 2 * g, tagged(M, tg), tagged(L, tg));
            }
            if ((n >> 1) == DBGN) TW(31);
            if ((n >> 1) == DBGN + 1) TW(2);
        }
    }
    TS(5);
    TW(9);
    TS2(15);
    if (threadIdx.x == 0) TSV(16, 2 * nend + 2);
    if (cta >= NROLE) return;

    uint32_t sl[6];
#pragma unroll
    for (int i = 0; i < 6; i++) sl[i] = sb + SM_RING + ((2 * nend + i) & 7) * TILE;
    const uint32_t bACT = sb + SM_ACT + (g * ACT_PITCH + 2 * t) * 2;
    const uint32_t wsw = (uint32_t)(warp >> 2);
    uint32_t aw[5][2][4];
    bool wo_ok = false;
    auto wo_frag = [&]() {
        const uint32_t ab = sb + SM_WREG + wsw * 2048 + kr * 128 + ((((warp & 3) * 2 + cs) ^ (kr & 7)) << 4);
#pragma unroll
        for (int i = 0; i < 5; i++)
            if (i < 4 || warp < 4) { ldsm4t(ab + i * 4096, aw[i][0]); ldsm4t(ab + i * 4096 + 9 * 2048, aw[i][1]); }
        wo_ok = true;
        TW(10);
    };
    {
        TW(8);
        while (jb < NB) job([&] { if (!wo_ok && __all_sync(0xffffffffu, mbar_test(bar_wo + 8 * min(lane, 2), 0))) wo_frag(); });

        TW(12);
        if (!wo_ok) {
            for (int i = 0; i < 3; i++) mbar_wait(bar_wo + 8 * i, 0);
            wo_frag();
        }
        cons_sync();
        TS(6);
        const uint32_t b00 = lds32(bACT), b01 = lds32(bACT + 16), b10 = lds32(bACT + 32), b11 = lds32(bACT + 48);
        unsigned* dst = g_wop + (size_t)cta * (DM * NB) + warp * 128 + lane * 4;
#pragma unroll
        for (int i = 0; i < 5; i++) {
            if (i < 4 || warp < 4) {
                float acc[4] = {0.f, 0.f, 0.f, 0.f};
                mma16816(acc, aw[i][0], b00, b01);
                mma16816(acc, aw[i][1], b10, b11);
                put_partial(dst + i * 1024, acc, tag2);
            }
        }
    }
    TS(17);
    TW(14);
    const int kq = warp & 3, tg = warp >> 2;
    uint32_t ag[3][9][4];
    if (cta < NRED) {
        uint4 rv[8];
        const unsigned* rp = red_ptr(g_wop, cta, warp, lane);
        red_issue(rp, rv);
        const float s = red_finish(rp, rv, tag2, sb, tid, 16);
        TS(19);
        if (tid < 64) {
            xin = bfr(xin + bfr(bf_lo(gab) * bfr(s)));
            const unsigned me = bf_bits(xin), other = __shfl_xor_sync(0xffffffffu, me, 16);
            if (lane < 16) stg_relaxed1(&g_x2[ob * (DM / 2) + (ocol >> 1)], (me | (other << 16)) + 1u);
        }
    }
    TW(17);
    {
#pragma unroll
        for (int i = 0; i < 3; i++) {
            mbar_wait(bar_gate + 8 * i, 0);
            mbar_wait(bar_full + 8 * ((2 * nend + i) & 7), ((2 * nend + i) >> 3) & 1);
        }
#pragma unroll
        for (int i = 0; i < 9; i++) {
            const int r0 = 144 * kq + 16 * i;
            const int box = r0 / 192;
            const uint32_t base = cs ? (sb + SM_RING + ((2 * nend + box) & 7) * TILE) : (sb + SM_WB + box * 15360);
            const uint32_t ab = base + (r0 - 192 * box + kr) * 80 + tg * 48;
            ldsm4t(ab, ag[0][i]);
            ldsm4t(ab + 16, ag[1][i]);
        }
        TW(15);
    }
    TS(8);
    if (tg == 0) {
#pragma unroll
        for (int i = 0; i < 9; i++) {
            const int r0 = 144 * kq + 16 * i;
            const int box = r0 / 192;
            const uint32_t base = cs ? (sb + SM_RING + ((2 * nend + box) & 7) * TILE) : (sb + SM_WB + box * 15360);
            ldsm4t(base + (r0 - 192 * box + kr) * 80 + 32, ag[2][i]);
        }
    }
    {
        unsigned xw[9];
        const unsigned* xp = g_x2 + warp * (DM / 2) + lane;
#pragma unroll
        for (int i = 0; i < 9; i++) xw[i] = ldg_relaxed1(xp + 32 * i);
        unsigned spins = 0;
        while (true) {
            bool ok = true;
#pragma unroll
            for (int i = 0; i < 9; i++)
                if (xw[i] == 0u) { xw[i] = ldg_relaxed1(xp + 32 * i); ok = false; }
            if (ok) break;
            if (++spins > SPIN_LIMIT) TRAP_AT(__LINE__);
        }
        __syncwarp();
        TS(20);
        TW(18);
#pragma unroll
        for (int i = 0; i < 9; i++) xw[i] -= 1u;
        unsigned mean2; float rsd;
        ln_stats(xw, mean2, rsd);
#pragma unroll
        for (int i = 0; i < 9; i++)
            sts32(bufA + (warp * BUFA_PITCH + 2 * (lane + 32 * i)) * 2, ln_apply(xw[i], mean2, rsd, cpk[i], spk[i]));
    }
    TW(19);
    cons_sync();
    TS(9);
    const uint32_t gred = sb + SM_RING + ((2 * nend + 6) & 7) * TILE;
    {
        float acc[3][4];
#pragma unroll
        for (int j = 0; j < 3; j++) acc[j][0] = acc[j][1] = acc[j][2] = acc[j][3] = 0.f;
#pragma unroll
        for (int i = 0; i < 9; i++) {
            const uint32_t b0 = lds32(bA + (9 * kq + i) * 32), b1 = lds32(bA + (9 * kq + i) * 32 + 16);
            mma16816(acc[0], ag[0][i], b0, b1);
            mma16816(acc[1], ag[1][i], b0, b1);
            if (tg == 0) mma16816(acc[2], ag[2][i], b0, b1);
        }
        const uint32_t ga = gred + ((kq * 5 + tg * 3) * 32 + lane) * 16;
        sts128f(ga, acc[0][0], acc[0][1], acc[0][2], acc[0][3]);
        sts128f(ga + 512, acc[1][0], acc[1][1], acc[1][2], acc[1][3]);
        if (tg == 0) sts128f(ga + 1024, acc[2][0], acc[2][1], acc[2][2], acc[2][3]);
    }
    TW(20);
    uint32_t ad[5][3][4];
    {
#pragma unroll
        for (int i = 3; i < 6; i++) mbar_wait(bar_full + 8 * ((2 * nend + i) & 7), ((2 * nend + i) >> 3) & 1);
#pragma unroll
        for (int ks = 0; ks < 3; ks++) {
            const int r = min(16 * ks + kr, 35);
            const uint32_t off = r * 128 + ((((warp & 3) * 2 + cs) ^ (r & 7)) << 4);
#pragma unroll
            for (int i = 0; i < 5; i++) {
                if (i < 4 || warp < 4) {
                    const int cb0 = 2 * i, cb1 = 2 * i + 1;
                    const uint32_t bx = wsw ? (sl[3 + (cb1 / 3 > 2 ? 2 : cb1 / 3)] + (cb1 % 3) * 5120) : (sl[3 + cb0 / 3] + (cb0 % 3) * 5120);
                    ldsm4t(bx + off, ad[i][ks]);
                }
            }
        }
    }
    TW(21);
    cons_sync();
    if (tid < 160) {
        const uint32_t ga = gred + tid * 16;
        float4 v = lds128f(ga);
#pragma unroll
        for (int k = 1; k < 4; k++) { const float4 u = lds128f(ga + k * 2560); v.x += u.x; v.y += u.y; v.z += u.z; v.w += u.w; }
        const int cl = 8 * warp + g - 4 * (cta & 1);
#pragma unroll
        for (int e = 0; e < 2; e++) {
            const float gt = bfr(e ? v.y : v.x), up = bfr(e ? v.w : v.z);
            const float inner = 0.7978845608028654f * fmaf(0.044715f * gt * gt, gt, gt);
            const float ge = bfr(gt * rcp(1.0f + ex2(inner * (-2.0f * LOG2E))));
            if (cl >= 0 && cl < 36) sts16(sb + SM_ACT + ((2 * t + e) * ACT_PITCH + cl) * 2, bf_bits(ge * up));
        }
    }
    TW(22);
    cons_sync();
    TS(10);
    {
        uint32_t b[3][2];
#pragma unroll
        for (int ks = 0; ks < 3; ks++) { b[ks][0] = lds32(bACT + ks * 32); b[ks][1] = lds32(bACT + ks * 32 + 16); }
        unsigned* dst = g_dnp + (size_t)cta * (DM * NB) + warp * 128 + lane * 4;
#pragma unroll
        for (int i = 0; i < 5; i++) {
            if (i < 4 || warp < 4) {
                float acc[4] = {0.f, 0.f, 0.f, 0.f};
#pragma unroll
                for (int ks = 0; ks < 3; ks++) mma16816(acc, ad[i][ks], b[ks][0], b[ks][1]);
                put_partial(dst + i * 1024, acc, tag2);
            }
        }
    }
    TS(11);
    TW(24);
    if (cta < NRED) {
        uint4 rv[8];
        const unsigned* rp = red_ptr(g_dnp, cta, warp, lane);
        red_issue(rp, rv);
        const float s = red_finish(rp, rv, tag2, sb, tid, 25);
        if (tid < 64) prm.out[ob * DM + ocol] = __float2bfloat16_rn(xin + bfr(bf_hi(gab) * bfr(s)));
    }
    TS(12);
    TW(26);
}

typedef CUresult (*EncodeFn)(CUtensorMap*, CUtensorMapDataType, cuuint32_t, void*, const cuuint64_t*, const cuuint64_t*,
                             const cuuint32_t*, const cuuint32_t*, CUtensorMapInterleave, CUtensorMapSwizzle,
                             CUtensorMapL2promotion, CUtensorMapFloatOOBfill);

bool make_map(EncodeFn fn, CUtensorMap* m, const void* ptr, uint64_t inner, uint64_t outer, uint64_t stride_bytes,
              uint32_t box_inner, uint32_t box_outer, CUtensorMapSwizzle sw, CUtensorMapL2promotion promo) {
    cuuint64_t dims[2] = {inner, outer};
    cuuint64_t strides[1] = {stride_bytes};
    cuuint32_t box[2] = {box_inner, box_outer};
    cuuint32_t es[2] = {1, 1};
    return fn(m, CU_TENSOR_MAP_DATA_TYPE_BFLOAT16, 2, const_cast<void*>(ptr), dims, strides, box, es,
              CU_TENSOR_MAP_INTERLEAVE_NONE, sw, promo, CU_TENSOR_MAP_FLOAT_OOB_FILL_NONE) == CUDA_SUCCESS;
}

}

extern "C" void kernel_launch(void* const* d_in, const int* in_sizes, int n_in, void* d_out, int out_size) {
    (void)in_sizes; (void)n_in; (void)out_size;
    static EncodeFn encode = nullptr;
    static int num_sms = 0;
    if (!encode) {
        void* fn = nullptr;
        cudaDriverEntryPointQueryResult qres;
        cudaGetDriverEntryPoint("cuTensorMapEncodeTiled", &fn, cudaEnableDefault, &qres);
        encode = (EncodeFn)fn;
        int dev = 0;
        cudaGetDevice(&dev);
        cudaDeviceGetAttribute(&num_sms, cudaDevAttrMultiProcessorCount, dev);
        cudaFuncSetAttribute(fused_kernel, cudaFuncAttributeMaxDynamicSharedMemorySize, SMEM_BYTES);
    }
    CUtensorMap tmK, tmV, tmQ, tmO, tmG, tmU, tmD;
    const uint64_t kvrows = (uint64_t)NPAIR * SK * 2;
    make_map(encode, &tmK, d_in[1], 64, kvrows, 128, 64, 128, CU_TENSOR_MAP_SWIZZLE_128B, CU_TENSOR_MAP_L2_PROMOTION_L2_256B);
    make_map(encode, &tmV, d_in[2], 64, kvrows, 128, 64, 128, CU_TENSOR_MAP_SWIZZLE_128B, CU_TENSOR_MAP_L2_PROMOTION_L2_256B);
    make_map(encode, &tmQ, d_in[3], 4096, DM, 8192, 32, 192, CU_TENSOR_MAP_SWIZZLE_64B, CU_TENSOR_MAP_L2_PROMOTION_L2_128B);
#define WPROMO CU_TENSOR_MAP_L2_PROMOTION_L2_128B
    make_map(encode, &tmO, d_in[4], DM, 4096, DM * 2, 64, 16, CU_TENSOR_MAP_SWIZZLE_128B, WPROMO);
    make_map(encode, &tmG, d_in[6], FF, DM, FF * 2, 40, 192, CU_TENSOR_MAP_SWIZZLE_NONE, WPROMO);
    make_map(encode, &tmU, d_in[7], FF, DM, FF * 2, 40, 192, CU_TENSOR_MAP_SWIZZLE_NONE, WPROMO);
    make_map(encode, &tmD, d_in[8], DM, FF, DM * 2, 64, 36, CU_TENSOR_MAP_SWIZZLE_128B, WPROMO);
    Params prm;
    prm.x = (const __nv_bfloat16*)d_in[0];
    prm.c = (const __nv_bfloat16*)d_in[9];
    prm.wmod = (const __nv_bfloat16*)d_in[10];
    prm.out = (__nv_bfloat16*)d_out;
    int grid = num_sms < MAXCTA ? num_sms : MAXCTA;
    fused_kernel<<<grid, NTHREADS, SMEM_BYTES>>>(tmK, tmV, tmQ, tmO, tmG, tmU, tmD, prm);
}
```

```cpp
#include <cuda_runtime.h>
#include <cuda_bf16.h>
#include <cuda.h>
#include <stdint.h>

namespace {

constexpr int NB = 8;
constexpr int DM = 576;
constexpr int SK = 8192;
constexpr int FF = 4608;
constexpr int NPAIR = 128;
constexpr int UKEYS = 64;
constexpr int UNITS = SK / UKEYS;
constexpr int U0 = 4;
constexpr int TILE = 16384;
constexpr int NTILE = 8;
#define INFL 4
#define INFL0 2
#define NRAMP 8
#define TINFL 2
#define WSTART 6
#define NCLR 48
#define NMOD 16
#define JD 6
#define DBGN 20
#define FINTHR 110
#define KVGATE 2
#define WEARLY 3
#define WQD 1
#define NCD 1200
constexpr int NROLE = 128;
constexpr int NRED = 72;
constexpr int MAXCTA = 132;
constexpr int RSTRIDE = 272;
constexpr int NTHREADS = 288;

constexpr int SM_RING = 0;
constexpr int SM_WREG = NTILE * TILE;
constexpr int SM_WB = SM_WREG + 36864;
constexpr int SM_BUFA = SM_WREG + 82944;
constexpr int BUFA_PITCH = 584;
constexpr int SM_RED = SM_BUFA + 8 * BUFA_PITCH * 2;
constexpr int SM_ACT = SM_RED + 4096;
constexpr int ACT_PITCH = 56;
constexpr int SM_ML = SM_ACT + 8 * ACT_PITCH * 2;
constexpr int SM_STAT = SM_ML + 128;
constexpr int SM_META = SM_STAT + 64;
constexpr int SM_BAR = SM_META + 32;
constexpr int SM_EPOCH = SM_BAR + 28 * 8;
constexpr int SM_SC = SM_EPOCH + 16;
constexpr int SM_TOTAL = SM_SC + 1280;
constexpr int SMEM_BYTES = SM_TOTAL + 1024;

__device__ __align__(128) unsigned g_fin[2][32];
__device__ __align__(128) unsigned g_tk[2][32];
__device__ __align__(128) unsigned g_cf[NPAIR * 8];
__device__ unsigned g_epoch;
__device__ unsigned g_started[2];
__device__ __align__(16) unsigned g_h[NB * DM];
__device__ __align__(16) unsigned g_mod[NB * 6 * DM];
__device__ __align__(16) unsigned g_q[NB * 4096];
__device__ __align__(128) unsigned long long g_part[(size_t)16 * UNITS * RSTRIDE];
__device__ __align__(128) unsigned g_wop[(size_t)NROLE * DM * NB];
__device__ __align__(128) unsigned g_x2[NB * DM / 2];
__device__ __align__(128) unsigned g_dnp[(size_t)NROLE * DM * NB];

struct Params {
    const __nv_bfloat16* x;
    const __nv_bfloat16* c;
    const __nv_bfloat16* wmod;
    __nv_bfloat16* out;
};

#define TRAP_AT(line) __trap()
#define TS(i)
#define TSL(i)
#define TS2(i)
#define TSP(i)
#define TSG(i, thr)
#define TSV(i, v)
#define TW(i)

__device__ __forceinline__ uint32_t smem_u32(const void* p) { return (uint32_t)__cvta_generic_to_shared(p); }
__device__ __forceinline__ void mbar_init(uint32_t bar, uint32_t cnt) {
    asm volatile("mbarrier.init.shared::cta.b64 [%0], %1;" ::"r"(bar), "r"(cnt) : "memory");
}
__device__ __forceinline__ void mbar_expect_tx(uint32_t bar, uint32_t bytes) {
    asm volatile("mbarrier.arrive.expect_tx.shared::cta.b64 _, [%0], %1;" ::"r"(bar), "r"(bytes) : "memory");
}
__device__ __forceinline__ void mbar_arrive(uint32_t bar) {
    asm volatile("mbarrier.arrive.shared::cta.b64 _, [%0];" ::"r"(bar) : "memory");
}
__device__ __forceinline__ bool mbar_try(uint32_t bar, uint32_t parity) {
    uint32_t ok;
    asm volatile(
        "{\n.reg .pred p;\n"
        "mbarrier.try_wait.parity.shared::cta.b64 p, [%1], %2;\n"
        "selp.u32 %0, 1, 0, p;\n}\n"
        : "=r"(ok) : "r"(bar), "r"(parity) : "memory");
    return ok != 0;
}
__device__ __forceinline__ bool mbar_test(uint32_t bar, uint32_t parity) {
    uint32_t ok;
    asm volatile(
        "{\n.reg .pred p;\n"
        "mbarrier.test_wait.parity.shared::cta.b64 p, [%1], %2;\n"
        "selp.u32 %0, 1, 0, p;\n}\n"
        : "=r"(ok) : "r"(bar), "r"(parity) : "memory");
    return ok != 0;
}
__device__ __noinline__ void mbar_wait_slow(uint32_t bar, uint32_t parity) {
    unsigned long long t0, t1;
    asm volatile("mov.u64 %0, %globaltimer;" : "=l"(t0));
    while (!mbar_try(bar, parity)) {
        asm volatile("mov.u64 %0, %globaltimer;" : "=l"(t1));
        if (t1 - t0 > 2000000000ull) TRAP_AT(__LINE__);
    }
}
__device__ __forceinline__ void mbar_wait(uint32_t bar, uint32_t parity) {
    if (!mbar_try(bar, parity)) mbar_wait_slow(bar, parity);
}
__device__ __forceinline__ void tma2d(uint32_t dst, const CUtensorMap* map, int c0, int c1, uint32_t bar) {
    asm volatile(
        "cp.async.bulk.tensor.2d.shared::cluster.global.mbarrier::complete_tx::bytes [%0], [%1, {%3, %4}], [%2];"
        ::"r"(dst), "l"((uint64_t)map), "r"(bar), "r"(c0), "r"(c1) : "memory");
}
__device__ __forceinline__ void tma2d_s(uint32_t dst, const CUtensorMap* map, int c0, int c1, uint32_t bar, uint64_t pol) {
    asm volatile(
        "cp.async.bulk.tensor.2d.shared::cluster.global.mbarrier::complete_tx::bytes.L2::cache_hint [%0], [%1, {%3, %4}], [%2], %5;"
        ::"r"(dst), "l"((uint64_t)map), "r"(bar), "r"(c0), "r"(c1), "l"(pol) : "memory");
}
__device__ __forceinline__ void prefetch_map(const CUtensorMap* map) {
    asm volatile("prefetch.tensormap [%0];" ::"l"((uint64_t)map) : "memory");
}
__device__ __forceinline__ void cp_async16(uint32_t dst, const void* src) {
    asm volatile("cp.async.cg.shared.global [%0], [%1], 16;" ::"r"(dst), "l"(src) : "memory");
}
__device__ __forceinline__ void ldsm4(uint32_t addr, uint32_t (&r)[4]) {
    asm volatile("ldmatrix.sync.aligned.m8n8.x4.shared.b16 {%0,%1,%2,%3}, [%4];"
                 : "=r"(r[0]), "=r"(r[1]), "=r"(r[2]), "=r"(r[3]) : "r"(addr) : "memory");
}
__device__ __forceinline__ void ldsm2(uint32_t addr, uint32_t& r0, uint32_t& r1) {
    asm volatile("ldmatrix.sync.aligned.m8n8.x2.shared.b16 {%0,%1}, [%2];" : "=r"(r0), "=r"(r1) : "r"(addr) : "memory");
}
__device__ __forceinline__ void ldsm4t(uint32_t addr, uint32_t (&r)[4]) {
    asm volatile("ldmatrix.sync.aligned.m8n8.x4.trans.shared.b16 {%0,%1,%2,%3}, [%4];"
                 : "=r"(r[0]), "=r"(r[1]), "=r"(r[2]), "=r"(r[3]) : "r"(addr) : "memory");
}
__device__ __forceinline__ void mma16816(float (&c)[4], const uint32_t (&a)[4], uint32_t b0, uint32_t b1) {
    asm volatile(
        "mma.sync.aligned.m16n8k16.row.col.f32.bf16.bf16.f32 {%0,%1,%2,%3}, {%4,%5,%6,%7}, {%8,%9}, {%0,%1,%2,%3};"
        : "+f"(c[0]), "+f"(c[1]), "+f"(c[2]), "+f"(c[3])
        : "r"(a[0]), "r"(a[1]), "r"(a[2]), "r"(a[3]), "r"(b0), "r"(b1));
}
__device__ __forceinline__ void cons_sync() { asm volatile("bar.sync 1, 256;" ::: "memory"); }
__device__ __forceinline__ void group_sync(int grp) { asm volatile("bar.sync %0, 128;" ::"r"(2 + grp) : "memory"); }
__device__ __forceinline__ uint32_t lds32(uint32_t addr) {
    uint32_t v; asm volatile("ld.shared.u32 %0, [%1];" : "=r"(v) : "r"(addr) : "memory"); return v;
}
__device__ __forceinline__ float2 lds64f(uint32_t addr) {
    float2 v; asm volatile("ld.shared.v2.f32 {%0,%1}, [%2];" : "=f"(v.x), "=f"(v.y) : "r"(addr) : "memory"); return v;
}
__device__ __forceinline__ float4 lds128f(uint32_t addr) {
    float4 v; asm volatile("ld.shared.v4.f32 {%0,%1,%2,%3}, [%4];" : "=f"(v.x), "=f"(v.y), "=f"(v.z), "=f"(v.w) : "r"(addr) : "memory"); return v;
}
__device__ __forceinline__ void sts32(uint32_t addr, unsigned v) {
    asm volatile("st.shared.u32 [%0], %1;" ::"r"(addr), "r"(v) : "memory");
}
__device__ __forceinline__ void sts16(uint32_t addr, unsigned v) {
    asm volatile("st.shared.u16 [%0], %1;" ::"r"(addr), "h"((unsigned short)v) : "memory");
}
__device__ __forceinline__ uint2 lds64u(uint32_t addr) {
    uint2 v; asm volatile("ld.shared.v2.u32 {%0,%1}, [%2];" : "=r"(v.x), "=r"(v.y) : "r"(addr) : "memory"); return v;
}
__device__ __forceinline__ void sts64f(uint32_t addr, float a, float b) {
    asm volatile("st.shared.v2.f32 [%0], {%1,%2};" ::"r"(addr), "f"(a), "f"(b) : "memory");
}
__device__ __forceinline__ void sts128f(uint32_t addr, float a, float b, float c, float d) {
    asm volatile("st.shared.v4.f32 [%0], {%1,%2,%3,%4};" ::"r"(addr), "f"(a), "f"(b), "f"(c), "f"(d) : "memory");
}
__device__ __forceinline__ uint2 ldg_relaxed2(const unsigned* p) {
    uint2 v; asm volatile("ld.relaxed.gpu.global.v2.u32 {%0,%1}, [%2];" : "=r"(v.x), "=r"(v.y) : "l"(p) : "memory"); return v;
}
__device__ __forceinline__ uint4 ldg_relaxed4(const unsigned* p) {
    uint4 v; asm volatile("ld.relaxed.gpu.global.v4.u32 {%0,%1,%2,%3}, [%4];"
                          : "=r"(v.x), "=r"(v.y), "=r"(v.z), "=r"(v.w) : "l"(p) : "memory"); return v;
}
__device__ __forceinline__ unsigned ldg_relaxed1(const unsigned* p) {
    unsigned v; asm volatile("ld.relaxed.gpu.global.u32 %0, [%1];" : "=r"(v) : "l"(p) : "memory"); return v;
}
__device__ __forceinline__ unsigned ldg_acquire1(const unsigned* p) {
    unsigned v; asm volatile("ld.acquire.gpu.global.u32 %0, [%1];" : "=r"(v) : "l"(p) : "memory"); return v;
}
__device__ __forceinline__ ulonglong2 ldg_relaxed64x2(const unsigned long long* p) {
    ulonglong2 v; asm volatile("ld.relaxed.gpu.global.v2.u64 {%0,%1}, [%2];" : "=l"(v.x), "=l"(v.y) : "l"(p) : "memory"); return v;
}
__device__ __forceinline__ void ldg_relaxed64x2_p(ulonglong2& v, const unsigned long long* p, bool pr) {
    asm volatile("{\n.reg .pred p;\nsetp.ne.u32 p, %3, 0;\n@p ld.relaxed.gpu.global.v2.u64 {%0,%1}, [%2];\n}\n"
                 : "+l"(v.x), "+l"(v.y) : "l"(p), "r"((unsigned)pr) : "memory");
}
__device__ __forceinline__ void stg_relaxed1(unsigned* p, unsigned v) {
    asm volatile("st.relaxed.gpu.global.u32 [%0], %1;" ::"l"(p), "r"(v) : "memory");
}
__device__ __forceinline__ void stg_relaxed4(unsigned* p, unsigned a, unsigned b, unsigned c, unsigned d) {
    asm volatile("st.relaxed.gpu.global.v4.u32 [%0], {%1,%2,%3,%4};" ::"l"(p), "r"(a), "r"(b), "r"(c), "r"(d) : "memory");
}
__device__ __forceinline__ unsigned long long tagged(float v, unsigned tag) {
    return ((unsigned long long)__float_as_uint(v) << 32) | tag;
}
__device__ __forceinline__ void stg_relaxed64x2(unsigned long long* p, unsigned long long a, unsigned long long b) {
    asm volatile("st.relaxed.gpu.global.v2.u64 [%0], {%1,%2};" ::"l"(p), "l"(a), "l"(b) : "memory");
}
__device__ __forceinline__ unsigned atom_add_lane0(unsigned* p, unsigned inc, int lane) {
    unsigned v = 0;
    asm volatile("{\n.reg .pred p;\nsetp.eq.s32 p, %3, 0;\n@p atom.relaxed.gpu.global.add.u32 %0, [%1], %2;\n}\n"
                 : "+r"(v) : "l"(p), "r"(inc), "r"(lane) : "memory");
    return v;
}
__device__ __forceinline__ float ex2(float x) { float y; asm("ex2.approx.ftz.f32 %0, %1;" : "=f"(y) : "f"(x)); return y; }
__device__ __forceinline__ float rcp(float x) { float y; asm("rcp.approx.ftz.f32 %0, %1;" : "=f"(y) : "f"(x)); return y; }

__device__ __forceinline__ float bfr(float x) { return __bfloat162float(__float2bfloat16_rn(x)); }
__device__ __forceinline__ unsigned bf_bits(float x) { return (unsigned)__bfloat16_as_ushort(__float2bfloat16_rn(x)); }
__device__ __forceinline__ float bf_hi(unsigned w) { return __uint_as_float(w & 0xffff0000u); }
__device__ __forceinline__ float bf_lo(unsigned w) { return __uint_as_float(w << 16); }
__device__ __forceinline__ unsigned pack_hi(unsigned lo_word, unsigned hi_word) {
    return __byte_perm(lo_word, hi_word, 0x7632);
}
__device__ __forceinline__ unsigned pack_bf2(float lo, float hi) {
    unsigned r; asm("cvt.rn.bf16x2.f32 %0, %1, %2;" : "=r"(r) : "f"(hi), "f"(lo)); return r;
}
__device__ __forceinline__ unsigned bf2_sub(unsigned a, unsigned b) { unsigned r; asm("sub.rn.bf16x2 %0, %1, %2;" : "=r"(r) : "r"(a), "r"(b)); return r; }
__device__ __forceinline__ unsigned bf2_mul(unsigned a, unsigned b) { unsigned r; asm("mul.rn.bf16x2 %0, %1, %2;" : "=r"(r) : "r"(a), "r"(b)); return r; }
__device__ __forceinline__ unsigned bf2_add(unsigned a, unsigned b) { unsigned r; asm("add.rn.bf16x2 %0, %1, %2;" : "=r"(r) : "r"(a), "r"(b)); return r; }
constexpr float LOG2E = 1.4426950408889634f;
constexpr float QSCALE = 0.08838834764831845f;
constexpr unsigned SPIN_LIMIT = 1u << 22;

template <int N>
__device__ __forceinline__ void fix_row16(const unsigned* base, int lane, unsigned tag16, uint2 (&v)[N]) {
    unsigned spins = 0;
    while (true) {
        bool ok = true;
#pragma unroll
        for (int i = 0; i < N; i++) {
            if ((v[i].x & 0xffffu) != tag16 || (v[i].y & 0xffffu) != tag16) {
                v[i] = ldg_relaxed2(base + 2 * (lane + 32 * i));
                ok = false;
            }
        }
        if (ok) break;
        if (++spins > SPIN_LIMIT) TRAP_AT(__LINE__);
    }
}
template <int N>
__device__ __forceinline__ void load_row16(const unsigned* base, int lane, uint2 (&v)[N]) {
#pragma unroll
    for (int i = 0; i < N; i++) v[i] = ldg_relaxed2(base + 2 * (lane + 32 * i));
}

__device__ __forceinline__ void ln_stats(const unsigned (&w)[9], unsigned& mean2, float& rsd) {
    const float sh = __shfl_sync(0xffffffffu, bf_lo(w[0]), 0);
    float s = 0.f, q = 0.f;
#pragma unroll
    for (int i = 0; i < 9; i++) {
        const float a = bf_lo(w[i]) - sh, b = bf_hi(w[i]) - sh;
        s += a + b;
        q = fmaf(a, a, q); q = fmaf(b, b, q);
    }
#pragma unroll
    for (int o = 16; o; o >>= 1) { s += __shfl_xor_sync(0xffffffffu, s, o); q += __shfl_xor_sync(0xffffffffu, q, o); }
    const float md = s * (1.0f / 576.0f);
    const float var = bfr(fmaxf(fmaf(-md, md, q * (1.0f / 576.0f)), 0.f));
    mean2 = pack_bf2(md + sh, md + sh);
    rsd = rcp(bfr(sqrtf(bfr(var + 1e-5f))));
}
__device__ __forceinline__ unsigned ln_apply(unsigned w, unsigned mean2, float rsd, unsigned c1, unsigned s) {
    const unsigned d = bf2_sub(w, mean2);
    const unsigned y = pack_bf2(bf_lo(d) * rsd, bf_hi(d) * rsd);
    return bf2_add(bf2_mul(y, c1), s);
}

__device__ __forceinline__ const unsigned* red_ptr(const unsigned* part, int cta, int warp, int lane) {
    return part + (size_t)(16 * warp + (lane >> 4)) * (DM * NB) + 64 * cta + 4 * (lane & 15);
}
__device__ __forceinline__ void red_issue(const unsigned* ptr, uint4 (&v)[8]) {
#pragma unroll
    for (int i = 0; i < 8; i++) v[i] = ldg_relaxed4(ptr + (size_t)(2 * i) * (DM * NB));
}
__device__ __forceinline__ float red_finish(const unsigned* ptr, uint4 (&v)[8], unsigned tag2, uint32_t sb, int tid, int twi) {
    const int warp = tid >> 5, lane = tid & 31;
    unsigned spins = 0;
    while (true) {
        bool ok = true;
#pragma unroll
        for (int i = 0; i < 8; i++) {
            if ((((v[i].x ^ tag2) | (v[i].y ^ tag2) | (v[i].z ^ tag2) | (v[i].w ^ tag2)) & 3u) != 0u) {
                v[i] = ldg_relaxed4(ptr + (size_t)(2 * i) * (DM * NB));
                ok = false;
            }
        }
        if (ok) break;
        if (++spins > SPIN_LIMIT) TRAP_AT(__LINE__);
    }
    __syncwarp();
    TW(twi);
    float f[4] = {0.f, 0.f, 0.f, 0.f};
#pragma unroll
    for (int i = 0; i < 8; i++) {
        f[0] += __uint_as_float(v[i].x); f[1] += __uint_as_float(v[i].y);
        f[2] += __uint_as_float(v[i].z); f[3] += __uint_as_float(v[i].w);
    }
#pragma unroll
    for (int e = 0; e < 4; e++) f[e] += __shfl_xor_sync(0xffffffffu, f[e], 16);
    if (lane < 16) sts128f(sb + SM_RED + (warp * 16 + lane) * 16, f[0], f[1], f[2], f[3]);
    cons_sync();
    float s = 0.f;
    if (tid < 64) {
        float r[8];
#pragma unroll
        for (int w = 0; w < 8; w++) r[w] = __uint_as_float(lds32(sb + SM_RED + (w * 64 + tid) * 4));
        s = ((r[0] + r[1]) + (r[2] + r[3])) + ((r[4] + r[5]) + (r[6] + r[7]));
    }
    return s;
}
__device__ __forceinline__ void put_partial(unsigned* dst, const float (&acc)[4], unsigned tag2) {
    stg_relaxed4(dst, (__float_as_uint(acc[0]) & ~3u) | tag2, (__float_as_uint(acc[1]) & ~3u) | tag2,
                 (__float_as_uint(acc[2]) & ~3u) | tag2, (__float_as_uint(acc[3]) & ~3u) | tag2);
}

__global__ void __launch_bounds__(NTHREADS, 1)
fused_kernel(const __grid_constant__ CUtensorMap tmK, const __grid_constant__ CUtensorMap tmV,
             const __grid_constant__ CUtensorMap tmQ,
             const __grid_constant__ CUtensorMap tmO, const __grid_constant__ CUtensorMap tmG,
             const __grid_constant__ CUtensorMap tmU, const __grid_constant__ CUtensorMap tmD,
             const Params prm) {
    extern __shared__ unsigned char smem_raw[];
    const uint32_t sb = (smem_u32(smem_raw) + 1023u) & ~1023u;
    unsigned char* sp = smem_raw + (sb - smem_u32(smem_raw));
    const int tid = threadIdx.x, lane = tid & 31, warp = tid >> 5;
    const int cta = blockIdx.x;
    const uint32_t bar_full = sb + SM_BAR, bar_empty = sb + SM_BAR + 64, bar_ctrl = sb + SM_BAR + 128;
    const uint32_t bar_wq = sb + SM_BAR + 160, bar_wo = bar_wq + 8, bar_gate = bar_wq + 32;
    volatile int2* meta = reinterpret_cast<volatile int2*>(sp + SM_META);
    volatile unsigned* s_epoch = reinterpret_cast<volatile unsigned*>(sp + SM_EPOCH);

    if (warp == 8) {
        if (lane == 0) {
            const unsigned e = ldg_relaxed1(&g_epoch);
            for (int i = 0; i < NTILE; i++) { mbar_init(bar_full + 8 * i, 1); mbar_init(bar_empty + 8 * i, 4); }
            for (int i = 0; i < 11; i++) mbar_init(bar_ctrl + 8 * i, 1);
            asm volatile("fence.mbarrier_init.release.cluster;" ::: "memory");
            asm volatile("fence.proxy.async.shared::cta;" ::: "memory");
            prefetch_map(&tmQ); prefetch_map(&tmK); prefetch_map(&tmV);
            if (WQD == 2) { const long long t0 = clock64(); while (clock64() - t0 < NCD) { } }
            if (WQD != 1) {
                if (cta < NROLE) {
                    mbar_expect_tx(bar_wq, 36864);
                    for (int i = 0; i < 3; i++) tma2d(sb + SM_WB + i * 12288, &tmQ, 32 * cta, 192 * i, bar_wq);
                } else {
                    mbar_arrive(bar_wq);
                }
            }
            *s_epoch = e;
        }
        TSG(24, 256);
        __syncthreads();
        if (WQD == 1 && lane == 0) {
            if (cta < NROLE) {
                mbar_expect_tx(bar_wq, 36864);
                for (int i = 0; i < 3; i++) tma2d(sb + SM_WB + i * 12288, &tmQ, 32 * cta, 192 * i, bar_wq);
            } else {
                mbar_arrive(bar_wq);
            }
        }
        const unsigned epoch = *s_epoch;
        const int par = epoch & 1;
        unsigned* ctr = &g_tk[par][0];
        uint64_t pol;
        asm volatile("createpolicy.fractional.L2::evict_first.b64 %0, 1.0;" : "=l"(pol));
        const unsigned nst = U0 * gridDim.x;
        unsigned pend = 0;
        int stage = 0;
        auto wchunk = [&](int i) {
            if (i < 3) {
                mbar_expect_tx(bar_wo + 8 * i, 12288);
                const int r0 = (cta >> 3) * 256 + (cta & 7) * 16;
                for (int r = 0; r < 6; r++) {
                    const int b = 6 * i + r;
                    const int rg = b >= 9, cb = b - 9 * rg;
                    tma2d(sb + SM_WREG + b * 2048, &tmO, 64 * cb, r0 + 128 * rg, bar_wo + 8 * i);
                }
            } else {
                mbar_expect_tx(bar_gate + 8 * (i - 3), 15360);
                tma2d(sb + SM_WB + (i - 3) * 15360, &tmG, (36 * cta) & ~7, 192 * (i - 3), bar_gate + 8 * (i - 3));
            }
        };
        auto advance = [&](bool block) {
            if (stage == 0) {
                if (cta < NROLE) {
                    unsigned* a = g_wop + (size_t)cta * (DM * NB);
                    unsigned* b = g_dnp + (size_t)cta * (DM * NB);
                    for (int i = lane; i < DM * NB / 4; i += 32) { stg_relaxed4(a + 4 * i, 0u, 0u, 0u, 0u); stg_relaxed4(b + 4 * i, 0u, 0u, 0u, 0u); }
                    if (cta < NRED) {
                        const int wcol = 8 * (cta >> 1) + 2 * (cta & 1) + 4 * ((lane >> 1) & 1) + (lane & 1);
                        stg_relaxed1(&g_x2[(lane >> 2) * (DM / 2) + wcol], 0u);
                    }
                }
                __syncwarp();
            } else if (stage == 1) {
                if (lane == 0) {
                    asm volatile("fence.acq_rel.gpu;" ::: "memory");
                    atomicAdd(&g_started[par], 1u);
                }
            } else if (stage == 2) {
                unsigned seen = 0;
                if (lane == 0) {
                    unsigned spins = 0;
                    while ((seen = ldg_acquire1(&g_started[par])) < gridDim.x && block) { if (++spins > SPIN_LIMIT) TRAP_AT(__LINE__); __nanosleep(100); }
                }
                if (__shfl_sync(0xffffffffu, seen, 0) < gridDim.x) return;
                if (lane == 0) {
                    if (cta == 0) {
                        g_started[par ^ 1] = 0;
                        g_epoch = epoch + 1;
                    }
                }
                __syncwarp();
                if (cta == 0 && lane == 0) { stg_relaxed1(&g_tk[par ^ 1][0], 0u); stg_relaxed1(&g_fin[par ^ 1][0], 0u); }
            }
            stage++;
        };
        int n = 0;
        for (;; n++) {
            const unsigned tk = (n < U0) ? (unsigned)n * gridDim.x + (unsigned)cta : __shfl_sync(0xffffffffu, pend, 0) + nst;
            if (tk >= (unsigned)(NPAIR * UNITS)) break;
            if (n >= U0 - 1) pend = atom_add_lane0(ctr, 1u, lane);
            const int iK = 2 * n;
            const int sK = iK & 7;
            const uint32_t eph = ((iK >> 3) & 1) ^ 1;
            mbar_wait(bar_empty + 8 * sK, eph);
            const int row = (int)tk * (UKEYS * 2);
            if (lane == 0) {
                meta[n & 3].x = (int)tk;
                mbar_arrive(bar_ctrl + 8 * (n & 3));
            }
            const int infl = (iK < NRAMP) ? INFL0 : INFL;
            if (KVGATE == 2 && iK == 0) mbar_wait(bar_wq, 0);
            if (KVGATE == 1 && iK == 2) mbar_wait(bar_wq, 0);
            if (iK >= infl) mbar_wait(bar_full + 8 * ((iK - infl) & 7), ((iK - infl) >> 3) & 1);
            if (lane == 0) {
                mbar_expect_tx(bar_full + 8 * sK, n >= U0 ? TILE + 1024 : TILE);
                tma2d_s(sb + SM_RING + sK * TILE, &tmK, 0, row, bar_full + 8 * sK, pol);
                if (n >= U0)
                    asm volatile("cp.async.bulk.shared::cluster.global.mbarrier::complete_tx::bytes [%0], [%1], 1024, [%2];"
                                 ::"r"(sb + SM_BUFA + (n & 3) * 1024), "l"(g_q + (tk >> 7) * 256), "r"(bar_full + 8 * sK) : "memory");
            }
            mbar_wait(bar_empty + 8 * (sK + 1), eph);
            if (iK + 1 >= infl) mbar_wait(bar_full + 8 * ((iK + 1 - infl) & 7), ((iK + 1 - infl) >> 3) & 1);
            if (lane == 0) {
                mbar_expect_tx(bar_full + 8 * (sK + 1), TILE);
                tma2d_s(sb + SM_RING + (sK + 1) * TILE, &tmV, 0, row, bar_full + 8 * (sK + 1), pol);
                if (cta < NROLE && n >= WSTART && n < WSTART + WEARLY) wchunk(n - WSTART);
            }
            __syncwarp();
            if ((stage == 0 && n >= NCLR) || (stage == 1 && n >= NCLR + 4) || (stage == 2 && n >= NCLR + 24 && (n & 7) == 0)) advance(false);
        }
        TSP(13);
        while (stage < 3) advance(true);
        if (lane == 0) {
            for (int e = 0; e < 2; e++) {
                const int ne = n + e;
                mbar_wait(bar_empty + 8 * ((2 * ne) & 7), (((2 * ne) >> 3) & 1) ^ 1);
                meta[ne & 3].x = -1 - n;
                mbar_arrive(bar_ctrl + 8 * (ne & 3));
            }
            if (cta < NROLE) {
                const int gc = (36 * cta) & ~7;
                const int early = min(max(0, n - WSTART), WEARLY);
                uint32_t hb[TINFL], hp[TINFL];
                bool released = false;
#pragma unroll
                for (int i = 0; i < TINFL; i++) {
                    const int it = 2 * n - TINFL + i;
                    hb[i] = bar_full + 8 * (it & 7); hp[i] = (it >> 3) & 1;
                }
#pragma unroll 1
                for (int i = 0; i < 12; i++) {
                    int kind, j;
                    if (i < 3) { kind = 0; j = i; }
                    else if (i < 9) { kind = (i - 3) & 1; j = kind ? ((i - 3) >> 1) : 3 + ((i - 3) >> 1); }
                    else { kind = 1; j = i - 6; }
                    if (kind == 0 && j < early) continue;
                    while (!released) {
                        const unsigned v = ldg_relaxed1(&g_fin[par][0]);
                        bool done = false;
#pragma unroll 1
                        for (int k = 0; k < 40 && !done; k++) done = mbar_test(hb[0], hp[0]);
                        if (done) break;
                        released = (v >= FINTHR);
                    }
#pragma unroll
                    for (int k = 0; k + 1 < TINFL; k++) { hb[k] = hb[k + 1]; hp[k] = hp[k + 1]; }
                    if (kind == 0) {
                        wchunk(j);
                        hb[TINFL - 1] = (j < 3) ? bar_wo + 8 * j : bar_gate + 8 * (j - 3); hp[TINFL - 1] = 0;
                    } else {
                        const int it = 2 * n + j;
                        const int s = it & 7;
                        const uint32_t dst = sb + SM_RING + s * TILE;
                        const uint32_t fb = bar_full + 8 * s;
                        mbar_wait(bar_empty + 8 * s, ((it >> 3) & 1) ^ 1);
                        if (j < 3) {
                            mbar_expect_tx(fb, 15360);
                            tma2d(dst, &tmU, gc, 192 * j, fb);
                        } else {
                            mbar_expect_tx(fb, 3 * 4608);
                            for (int r = 0; r < 3; r++) tma2d(dst + r * 5120, &tmD, 64 * (3 * (j - 3) + r), 36 * cta, fb);
                        }
                        hb[TINFL - 1] = fb; hp[TINFL - 1] = (it >> 3) & 1;
                    }
                }
            }
        }
        TSG(26, 256);
        return;
    }

    const int g = lane >> 2, t = lane & 3;
    TS(0);
    TW(0);
    const uint32_t bufA = sb + SM_BUFA;
    const uint32_t bA = bufA + (g * BUFA_PITCH + 2 * t) * 2;
    const int kr = (lane & 7) + 8 * (lane >> 4), cs = (lane >> 3) & 1;
    constexpr int SM_RED2 = SM_WREG + 73728;
    const bool crit = cta < NRED;
    const int c00 = crit ? 8 * cta : 1152 + 32 * (cta - NRED);
    const int c01 = crit ? DM + 8 * cta : c00 + 8;
    const int c1 = crit ? (cta < 32 ? 1152 + 16 * (112 + cta) : -1) : c00 + 16;
    float x0 = 0.f, x1 = 0.f;
    if (cta < NROLE) {
        const unsigned* cw = reinterpret_cast<const unsigned*>(prm.c) + warp * 288;
        unsigned cv[9], xw[9];
#pragma unroll
        for (int i = 0; i < 9; i++) cv[i] = __ldg(cw + lane + 32 * i);
        if (crit) {
#pragma unroll
            for (int i = 0; i < 9; i++) xw[i] = __ldg(reinterpret_cast<const unsigned*>(prm.x) + warp * 288 + lane + 32 * i);
            if (warp == 0) {
                x0 = __bfloat162float(prm.x[(2 * t) * DM + 8 * cta + g]);
                x1 = __bfloat162float(prm.x[(2 * t + 1) * DM + 8 * cta + g]);
            }
#pragma unroll
            for (int i = 0; i < 5; i++) {
                const int q = tid + 256 * i;
                const int r = q >> 1, ch = q & 1;
                if (q < 1152) cp_async16(sb + SM_WREG + r * 32 + ((ch ^ ((r >> 2) & 1)) << 4), prm.wmod + (size_t)r * 3456 + (ch ? c01 : c00));
            }
        }
        asm volatile("cp.async.commit_group;" ::: "memory");
        if (warp == 1) {
#pragma unroll
            for (int i = 0; i < 2; i++) stg_relaxed4(&g_q[(4 * i + g / 2) * 4096 + 32 * cta + 4 * (lane & 7)], 0u, 0u, 0u, 0u);
        } else if (warp == 2) {
            if (crit && lane < 16) stg_relaxed4(&g_h[(lane >> 1) * DM + 8 * cta + 4 * (lane & 1)], 0u, 0u, 0u, 0u);
            for (int i = lane; i < 48; i += 32) sts32(sb + SM_ACT + ((i / 6) * ACT_PITCH + 36 + 2 * (i % 6)) * 2, 0u);
        }
#pragma unroll
        for (int i = 0; i < 9; i++) {
            const float a = bf_lo(cv[i]), b = bf_hi(cv[i]);
            sts32(bufA + (warp * BUFA_PITCH + 2 * (lane + 32 * i)) * 2,
                  pack_bf2(a * rcp(1.0f + ex2(-a * LOG2E)), b * rcp(1.0f + ex2(-b * LOG2E))));
        }
        if (crit) {
            unsigned mean2; float rsd;
            ln_stats(xw, mean2, rsd);
            if (lane == 0) sts64f(sb + SM_STAT + 8 * warp, bf_lo(mean2), rsd);
        }
        if (!crit) {
#pragma unroll
            for (int i = 0; i < 9; i++) {
                const int q = tid + 256 * i;
                const int r = q >> 2, ch = q & 1, tl = (q >> 1) & 1;
                cp_async16(sb + SM_WREG + tl * 18432 + r * 32 + ((ch ^ ((r >> 2) & 1)) << 4), prm.wmod + (size_t)r * 3456 + c00 + 8 * (q & 3));
            }
        } else if (c1 >= 0) {
#pragma unroll
            for (int i = 0; i < 5; i++) {
                const int q = tid + 256 * i;
                const int r = q >> 1, ch = q & 1;
                if (q < 1152) cp_async16(sb + SM_WREG + 18432 + r * 32 + ((ch ^ ((r >> 2) & 1)) << 4), prm.wmod + (size_t)r * 3456 + c1 + 8 * ch);
            }
        }
        asm volatile("cp.async.commit_group;" ::: "memory");
        asm volatile("cp.async.wait_group 1;" ::: "memory");
    }
    __syncthreads();
    const unsigned epoch = *s_epoch;
    TW(1);
    const int par = epoch & 1;
    const unsigned tag16 = epoch % 65535u + 1u;
    const unsigned tag2 = epoch % 3u + 1u;

    if (cta < NROLE) {
        uint32_t mb[5][2];
#pragma unroll
        for (int i = 0; i < 5; i++) {
            mb[i][0] = mb[i][1] = 0u;
            if (i < 4 || warp < 4) { mb[i][0] = lds32(bA + (warp + 8 * i) * 32); mb[i][1] = lds32(bA + (warp + 8 * i) * 32 + 16); }
        }
        auto mod_mma = [&](uint32_t tb, uint32_t red) {
            float acc[4] = {0.f, 0.f, 0.f, 0.f};
            const uint32_t ab = tb + kr * 32 + ((cs ^ ((kr >> 2) & 1)) << 4) + warp * 512;
            uint32_t a[5][4];
#pragma unroll
            for (int i = 0; i < 5; i++)
                if (i < 4 || warp < 4) ldsm4t(ab + i * 4096, a[i]);
#pragma unroll
            for (int i = 0; i < 5; i++)
                if (i < 4 || warp < 4) mma16816(acc, a[i], mb[i][0], mb[i][1]);
            sts128f(red + tid * 16, acc[0], acc[1], acc[2], acc[3]);
        };
        auto mod_sum = [&](uint32_t red) {
            float4 u[8];
#pragma unroll
            for (int k = 0; k < 8; k++) u[k] = lds128f(red + (k * 32 + lane) * 16);
            float4 v;
            v.x = ((u[0].x + u[1].x) + (u[2].x + u[3].x)) + ((u[4].x + u[5].x) + (u[6].x + u[7].x));
            v.y = ((u[0].y + u[1].y) + (u[2].y + u[3].y)) + ((u[4].y + u[5].y) + (u[6].y + u[7].y));
            v.z = ((u[0].z + u[1].z) + (u[2].z + u[3].z)) + ((u[4].z + u[5].z) + (u[6].z + u[7].z));
            v.w = ((u[0].w + u[1].w) + (u[2].w + u[3].w)) + ((u[4].w + u[5].w) + (u[6].w + u[7].w));
            return v;
        };
        auto mod_put = [&](const float4 v, int col) {
            stg_relaxed1(&g_mod[(2 * t) * 3456 + col + g], (bf_bits(v.x) << 16) | tag16);
            stg_relaxed1(&g_mod[(2 * t + 1) * 3456 + col + g], (bf_bits(v.y) << 16) | tag16);
            stg_relaxed1(&g_mod[(2 * t) * 3456 + col + 8 + g], (bf_bits(v.z) << 16) | tag16);
            stg_relaxed1(&g_mod[(2 * t + 1) * 3456 + col + 8 + g], (bf_bits(v.w) << 16) | tag16);
        };
        if (crit) mod_mma(sb + SM_WREG, sb + SM_RED);
        cons_sync();
        if (crit && warp == 0) {
            const float4 v = mod_sum(sb + SM_RED);
            const float4 st = lds128f(sb + SM_STAT + 16 * t);
            const float y0 = bfr(bfr(x0 - st.x) * st.y), y1 = bfr(bfr(x1 - st.z) * st.w);
            const float h0 = bfr(y0 * bfr(1.0f + bfr(v.z))) + bfr(v.x);
            const float h1 = bfr(y1 * bfr(1.0f + bfr(v.w))) + bfr(v.y);
            stg_relaxed1(&g_h[(2 * t) * DM + 8 * cta + g], (bf_bits(h0) << 16) | tag16);
            stg_relaxed1(&g_h[(2 * t + 1) * DM + 8 * cta + g], (bf_bits(h1) << 16) | tag16);
        }
        TS(1);
        TW(2);
        mbar_wait(bar_wq, 0);
        const int tile = warp & 1, kq = warp >> 1;
        uint32_t aq[9][4];
        {
            const uint32_t ab = sb + SM_WB + (144 * kq + kr) * 64 + (((2 * tile + cs) ^ ((kr >> 1) & 3)) << 4);
#pragma unroll
            for (int i = 0; i < 9; i++) ldsm4t(ab + i * 1024, aq[i]);
        }
        TW(3);
        uint2 hv[9];
        load_row16<9>(g_h + warp * DM, lane, hv);
        fix_row16<9>(g_h + warp * DM, lane, tag16, hv);
        __syncwarp();
        TW(4);
#pragma unroll
        for (int i = 0; i < 9; i++) sts32(bufA + (warp * BUFA_PITCH + 2 * (lane + 32 * i)) * 2, pack_hi(hv[i].x, hv[i].y));
        cons_sync();
        float acc0[4] = {0.f, 0.f, 0.f, 0.f}, acc1[4] = {0.f, 0.f, 0.f, 0.f};
#pragma unroll
        for (int i = 0; i < 9; i++) {
            const uint32_t b0 = lds32(bA + (9 * kq + i) * 32), b1 = lds32(bA + (9 * kq + i) * 32 + 16);
            if (i & 1) mma16816(acc1, aq[i], b0, b1); else mma16816(acc0, aq[i], b0, b1);
        }
        sts128f(sb + SM_RED + tid * 16, acc0[0] + acc1[0], acc0[1] + acc1[1], acc0[2] + acc1[2], acc0[3] + acc1[3]);
        asm volatile("fence.proxy.async.shared::cta;" ::: "memory");
        cons_sync();
        if (warp < 2) {
            float4 v = lds128f(sb + SM_RED + (warp * 32 + lane) * 16);
#pragma unroll
            for (int k = 1; k < 4; k++) { const float4 u = lds128f(sb + SM_RED + ((warp + 2 * k) * 32 + lane) * 16); v.x += u.x; v.y += u.y; v.z += u.z; v.w += u.w; }
            const int col = 32 * cta + 16 * warp + g;
            stg_relaxed1(&g_q[(2 * t) * 4096 + col], (bf_bits(v.x) << 16) | tag16);
            stg_relaxed1(&g_q[(2 * t + 1) * 4096 + col], (bf_bits(v.y) << 16) | tag16);
            stg_relaxed1(&g_q[(2 * t) * 4096 + col + 8], (bf_bits(v.z) << 16) | tag16);
            stg_relaxed1(&g_q[(2 * t + 1) * 4096 + col + 8], (bf_bits(v.w) << 16) | tag16);
        }
        TW(13);
        if (c1 >= 0) {
            asm volatile("cp.async.wait_group 0;" ::: "memory");
            cons_sync();
            if (!crit) mod_mma(sb + SM_WREG, sb + SM_RED2 + 4096);
            mod_mma(sb + SM_WREG + 18432, sb + SM_RED2);
            asm volatile("fence.proxy.async.shared::cta;" ::: "memory");
            cons_sync();
            if (warp == 2) mod_put(mod_sum(sb + SM_RED2), c1);
            if (warp == 3 && !crit) mod_put(mod_sum(sb + SM_RED2 + 4096), c00);
        }
    }
    TS(2);
    TW(5);
    const int ocol = 16 * (cta >> 1) + 4 * (cta & 1) + ((tid >> 4) & 3) + 8 * ((tid >> 1) & 1);
    const int ob = 2 * ((tid >> 2) & 3) + (tid & 1);
    const bool oth = cta < NRED && tid < 64;
    unsigned gab = 0; float xin = 0.f;

    const int grp = warp >> 2, wq = warp & 3;
    int n = grp;
    int nend = 0;
    int jb = (cta < NROLE) ? grp : NB;
    const int hk = (cta >> 3) & 15;
    const unsigned tagF = epoch % 0xfffffffeu + 1u;
    auto job = [&](auto hook) {
        const unsigned tg = (epoch * 8u + (unsigned)jb) % 0xfffffffeu + 1u;
        const int half = lane >> 4;
        const unsigned long long* rec = g_part + (size_t)(hk * UNITS + 32 * wq) * RSTRIDE;
        const unsigned long long* pd = rec + half * RSTRIDE + 2 * ((cta & 7) * 16 + (lane & 15));
        const unsigned long long* ph2 = rec + (lane >> 1) * RSTRIDE + 256 + 2 * (lane & 1);
        ulonglong2 w[16], hd[2];
#pragma unroll
        for (int i = 0; i < 16; i++) w[i] = make_ulonglong2(0ull, 0ull);
        hd[0] = hd[1] = make_ulonglong2(0ull, 0ull);
        unsigned got = 0, spins = 0;
        while (true) {
            ldg_relaxed64x2_p(hd[0], ph2, !((got >> 16) & 1u));
            ldg_relaxed64x2_p(hd[1], ph2 + 16 * RSTRIDE, !((got >> 17) & 1u));
#pragma unroll
            for (int i = 0; i < 16; i++) ldg_relaxed64x2_p(w[i], pd + 2 * i * RSTRIDE, !((got >> i) & 1u));
            hook();
#pragma unroll
            for (int i = 0; i < 2; i++)
                if ((unsigned)hd[i].x == tg && (unsigned)hd[i].y == tg) got |= 1u << (16 + i);
#pragma unroll
            for (int i = 0; i < 16; i++)
                if ((unsigned)w[i].x == tg && (unsigned)w[i].y == tg) got |= 1u << i;
            if (__all_sync(0xffffffffu, got == 0x3ffffu)) break;
            if (++spins > SPIN_LIMIT) TRAP_AT(__LINE__);
        }
        TW(11);
        const float m0 = __uint_as_float((unsigned)(hd[0].x >> 32)), m1 = __uint_as_float((unsigned)(hd[1].x >> 32));
        float M = fmaxf(m0, m1);
#pragma unroll
        for (int of = 2; of <= 16; of <<= 1) M = fmaxf(M, __shfl_xor_sync(0xffffffffu, M, of));
        const float f0 = ex2((m0 - M) * LOG2E), f1 = ex2((m1 - M) * LOG2E);
        const uint32_t fs = sb + SM_RED + warp * 256;
        const uint32_t fo = fs + ((((lane >> 1) & 1) * 32 + (lane >> 2) * 2 + (lane & 1)) << 2);
        sts32(fo, __float_as_uint(f0));
        sts32(fo + 64, __float_as_uint(f1));
        float L = f0 * __uint_as_float((unsigned)(hd[0].y >> 32)) + f1 * __uint_as_float((unsigned)(hd[1].y >> 32));
        __syncwarp();
#pragma unroll
        for (int of = 2; of <= 16; of <<= 1) L += __shfl_xor_sync(0xffffffffu, L, of);
        float a0 = 0.f, a1 = 0.f;
#pragma unroll
        for (int k = 0; k < 8; k++) {
            const float4 ff = lds128f(fs + half * 128 + k * 16);
            a0 = fmaf(ff.x, __uint_as_float((unsigned)(w[2 * k].x >> 32)), a0);
            a1 = fmaf(ff.y, __uint_as_float((unsigned)(w[2 * k].y >> 32)), a1);
            a0 = fmaf(ff.z, __uint_as_float((unsigned)(w[2 * k + 1].x >> 32)), a0);
            a1 = fmaf(ff.w, __uint_as_float((unsigned)(w[2 * k + 1].y >> 32)), a1);
        }
        const float v = (half ? a1 : a0) + __shfl_xor_sync(0xffffffffu, half ? a0 : a1, 16);
        const int alt = grp * 2 + ((jb >> 1) & 1);
        const uint32_t pv = sb + SM_RED + 2048 + alt * 512, pm = sb + SM_SC + 1024 + alt * 64;
        sts32(pv + wq * 128 + lane * 4, __float_as_uint(v));
        if (lane < 2) sts64f(pm + wq * 16 + lane * 8, M, L);
        group_sync(grp);
        if (wq == 0) {
            float mw[4], lw[4], vw[4];
#pragma unroll
            for (int k = 0; k < 4; k++) {
                const float4 q4 = lds128f(pm + k * 16);
                mw[k] = half ? q4.z : q4.x; lw[k] = half ? q4.w : q4.y;
                vw[k] = __uint_as_float(lds32(pv + k * 128 + lane * 4));
            }
            const float Mx = fmaxf(fmaxf(mw[0], mw[1]), fmaxf(mw[2], mw[3]));
            float num = 0.f, den = 0.f;
#pragma unroll
            for (int k = 0; k < 4; k++) { const float f = ex2((mw[k] - Mx) * LOG2E); num = fmaf(f, vw[k], num); den = fmaf(f, lw[k], den); }
            sts16(sb + SM_ACT + (jb * ACT_PITCH + lane) * 2, bf_bits(__fdividef(num, den)));
            } else if (wq == 1 && lane == 0 && jb < NB - 1) {
                asm volatile("st.release.gpu.global.u32 [%0], %1;" ::"l"(&g_cf[(16 * jb + hk) * 8 + (cta & 7)]), "r"(tagF) : "memory");
        }
        jb += 2;
    };
    {
        uint32_t kpre[2], vpre[2];
        {
            const int key = (lane & 7) + 8 * ((lane >> 3) & 1), kc = lane >> 4;
#pragma unroll
            for (int h = 0; h < 2; h++) {
                const int r = 2 * (16 * wq + key) + h;
                kpre[h] = r * 128 + ((kc ^ (r & 7)) << 4);
            }
            const int k7 = (lane & 7), hi = lane >> 4, cv = (lane >> 3) & 1;
            const int vkey = (k7 >> 1) + 8 * (k7 & 1) + 4 * hi;
            const int r = 2 * vkey + (wq >> 1);
#pragma unroll
            for (int i = 0; i < 2; i++) vpre[i] = (r * 128 + ((cv ^ (r & 7)) << 4)) ^ (((2 * wq + i) & 3) << 5);
        }
        bool mod_done = cta >= NROLE;
        for (;; n += 2) {
            const uint32_t ph = (n >> 2) & 1;
            mbar_wait(bar_ctrl + 8 * (n & 3), ph);
            const int tk = meta[n & 3].x, np = tk >> 7;
            if ((n >> 1) == DBGN) TW(23);
            if (!mod_done && (n >= NMOD || tk < 0)) {
                mod_done = true;
                if (oth) {
                    unsigned gaw, gbw, spins = 0;
                    xin = __bfloat162float(prm.x[ob * DM + ocol]);
                    do {
                        gaw = ldg_relaxed1(&g_mod[ob * 3456 + 2 * DM + ocol]);
                        gbw = ldg_relaxed1(&g_mod[ob * 3456 + 5 * DM + ocol]);
                        if (++spins > SPIN_LIMIT) TRAP_AT(__LINE__);
                    } while ((gaw & 0xffffu) != tag16 || (gbw & 0xffffu) != tag16);
                    gab = pack_hi(gaw, gbw);
                }
            }
            if (tk < 0) { nend = -1 - tk; break; }
            while (jb < NB && np >= 16 * jb + hk + JD) job([] {});
            uint32_t qf[8][2];
            unsigned fl = tagF;
            if (np >= 16 && lane < 8) fl = ldg_relaxed1(&g_cf[(np - 16) * 8 + lane]);
            const int sK = (2 * n) & 7;
            const uint32_t kb = sb + SM_RING + sK * TILE, vb = kb + TILE;
            {
                uint2 qa[8], qb2[8];
                const uint32_t qs0 = sb + SM_BUFA + (n & 3) * 1024, qs = qs0 + ((g & 1) * 128 + 2 * t) * 4;
                bool ok = false;
                if (n >= U0) {
                    mbar_wait(bar_full + 8 * sK, ph);
                    ok = true;
#pragma unroll
                    for (int ks = 0; ks < 8; ks++) {
                        qa[ks] = lds64u(qs + 64 * ks); qb2[ks] = lds64u(qs + 64 * ks + 32);
                        ok = ok && ((qa[ks].x & 0xffffu) == tag16) && ((qa[ks].y & 0xffffu) == tag16) &&
                             ((qb2[ks].x & 0xffffu) == tag16) && ((qb2[ks].y & 0xffffu) == tag16);
                    }
                    ok = __all_sync(0xffffffffu, ok);
                }
                if (!ok) {
                    if (n >= U0) group_sync(grp);
                    const unsigned* qb = g_q + np * 256 + 4 * lane;
                    unsigned spins = 0;
                    uint4 x0, x1;
                    while (true) {
                        x0 = ldg_relaxed4(qb); x1 = ldg_relaxed4(qb + 128);
                        const unsigned e = ((x0.x ^ tag16) | (x0.y ^ tag16) | (x0.z ^ tag16) | (x0.w ^ tag16) |
                                            (x1.x ^ tag16) | (x1.y ^ tag16) | (x1.z ^ tag16) | (x1.w ^ tag16)) & 0xffffu;
                        if (__all_sync(0xffffffffu, e == 0u)) break;
                        if (++spins > SPIN_LIMIT) TRAP_AT(__LINE__);
                    }
                    sts128f(qs0 + 16 * lane, __uint_as_float(x0.x), __uint_as_float(x0.y), __uint_as_float(x0.z), __uint_as_float(x0.w));
                    sts128f(qs0 + 512 + 16 * lane, __uint_as_float(x1.x), __uint_as_float(x1.y), __uint_as_float(x1.z), __uint_as_float(x1.w));
                    asm volatile("fence.proxy.async.shared::cta;" ::: "memory");
                    __syncwarp();
#pragma unroll
                    for (int ks = 0; ks < 8; ks++) { qa[ks] = lds64u(qs + 64 * ks); qb2[ks] = lds64u(qs + 64 * ks + 32); }
                }
#pragma unroll
                for (int ks = 0; ks < 8; ks++) { qf[ks][0] = pack_hi(qa[ks].x, qa[ks].y); qf[ks][1] = pack_hi(qb2[ks].x, qb2[ks].y); }
            }
            if ((n >> 1) == DBGN) TW(27);
            if (n == 0) TS(3);
            if (n < 2) TW(6);
            if (n == 4 || n == 5) TW(7);
            if (n == 4) TS(4);
            mbar_wait(bar_full + 8 * sK, ph);
            if ((n >> 1) == DBGN) TW(28);
            float c0[4] = {0.f, 0.f, 0.f, 0.f}, c1a[4] = {0.f, 0.f, 0.f, 0.f};
#pragma unroll
            for (int ks = 0; ks < 8; ks += 2) {
                uint32_t a[4], b[4];
                ldsm4(kb + (kpre[ks >> 2] ^ ((ks & 3) << 5)), a);
                ldsm4(kb + (kpre[(ks + 1) >> 2] ^ (((ks + 1) & 3) << 5)), b);
                mma16816(c0, a, qf[ks][0], qf[ks][1]);
                mma16816(c1a, b, qf[ks + 1][0], qf[ks + 1][1]);
            }
            __syncwarp();
            if (lane == 0) mbar_arrive(bar_empty + 8 * sK);
            float s0 = (t & 1) ? (c0[1] + c1a[1]) : (c0[0] + c1a[0]);
            float s1 = (t & 1) ? (c0[3] + c1a[3]) : (c0[2] + c1a[2]);
            s0 = bfr(bfr(s0) * QSCALE);
            s1 = bfr(bfr(s1) * QSCALE);
            const uint32_t ssc = sb + SM_SC + grp * 512 + ((n >> 1) & 1) * 256;
            if (t < 2) sts32(ssc + (((t * 4 + (g & 3)) * 8 + wq * 2 + (g >> 2)) << 2), pack_hi(__float_as_uint(s0), __float_as_uint(s1)));
            group_sync(grp);
            if ((n >> 1) == DBGN) TW(29);
            uint32_t pb[8];
            {
                const float4 x0 = lds128f(ssc + ((g & 1) * 4 + t) * 32), x1 = lds128f(ssc + ((g & 1) * 4 + t) * 32 + 16);
                pb[0] = __float_as_uint(x0.x); pb[1] = __float_as_uint(x0.y); pb[2] = __float_as_uint(x0.z); pb[3] = __float_as_uint(x0.w);
                pb[4] = __float_as_uint(x1.x); pb[5] = __float_as_uint(x1.y); pb[6] = __float_as_uint(x1.z); pb[7] = __float_as_uint(x1.w);
            }
            float M = -INFINITY, L = 0.f;
#pragma unroll
            for (int i = 0; i < 8; i++) M = fmaxf(M, fmaxf(bf_lo(pb[i]), bf_hi(pb[i])));
            M = fmaxf(M, __shfl_xor_sync(0xffffffffu, M, 1));
            M = fmaxf(M, __shfl_xor_sync(0xffffffffu, M, 2));
#pragma unroll
            for (int i = 0; i < 8; i++) {
                const float p0 = ex2((bf_lo(pb[i]) - M) * LOG2E), p1 = ex2((bf_hi(pb[i]) - M) * LOG2E);
                L += p0 + p1;
                pb[i] = pack_bf2(p0, p1);
            }
            L += __shfl_xor_sync(0xffffffffu, L, 1);
            L += __shfl_xor_sync(0xffffffffu, L, 2);
            float o[2][4] = {{0.f, 0.f, 0.f, 0.f}, {0.f, 0.f, 0.f, 0.f}};
            mbar_wait(bar_full + 8 * (sK + 1), ph);
            if ((n >> 1) == DBGN) TW(30);
#pragma unroll
            for (int ks = 0; ks < 4; ks++) {
                uint32_t a[4], b[4];
                ldsm4t(vb + vpre[0] + ks * 4096, a);
                ldsm4t(vb + vpre[1] + ks * 4096, b);
                mma16816(o[0], a, pb[2 * ks], pb[2 * ks + 1]);
                mma16816(o[1], b, pb[2 * ks], pb[2 * ks + 1]);
            }
            __syncwarp();
            if (lane == 0) mbar_arrive(bar_empty + 8 * (sK + 1));
            {
                unsigned spins = 0;
                while (!__all_sync(0xffffffffu, fl == tagF)) {
                    if (++spins > SPIN_LIMIT) TRAP_AT(__LINE__);
                    if (lane < 8) fl = ldg_relaxed1(&g_cf[(np - 16) * 8 + lane]);
                }
            }
            {
                const unsigned tg = (epoch * 8u + (unsigned)(np >> 4)) % 0xfffffffeu + 1u;
                unsigned long long* rec = g_part + (size_t)(tk & (16 * UNITS - 1)) * RSTRIDE;
                const float u0 = (t & 2) ? o[1][0] : o[0][0], u1 = (t & 2) ? o[1][1] : o[0][1];
                const float u2 = (t & 2) ? o[1][2] : o[0][2], u3 = (t & 2) ? o[1][3] : o[0][3];
                const int d = 32 * wq + 8 * t + g;
                stg_relaxed64x2(rec + 2 * d, tagged((t & 1) ? u2 : u0, tg), tagged((t & 1) ? u3 : u1, tg));
                if (wq == 0 && t == 0 && g < 2) stg_relaxed64x2(rec + 256 + 2 * g, tagged(M, tg), tagged(L, tg));
            }
            if ((n >> 1) == DBGN) TW(31);
            if ((n >> 1) == DBGN + 1) TW(2);
        }
    }
    TS(5);
    if (threadIdx.x == 0) atomicAdd(&g_fin[epoch & 1][0], 1u);
    TW(9);
    TS2(15);
    if (threadIdx.x == 0) TSV(16, 2 * nend + 2);
    if (cta >= NROLE) return;

    const uint32_t bACT = sb + SM_ACT + (g * ACT_PITCH + 2 * t) * 2;
    const uint32_t wsw = (uint32_t)(warp >> 2);
    uint32_t aw[5][2][4];
    bool wo_ok = false;
    auto wo_frag = [&]() {
        const uint32_t ab = sb + SM_WREG + wsw * 2048 + kr * 128 + ((((warp & 3) * 2 + cs) ^ (kr & 7)) << 4);
#pragma unroll
        for (int i = 0; i < 5; i++)
            if (i < 4 || warp < 4) { ldsm4t(ab + i * 4096, aw[i][0]); ldsm4t(ab + i * 4096 + 9 * 2048, aw[i][1]); }
        wo_ok = true;
        TW(10);
    };
    {
        TW(8);
        while (jb < NB) job([&] { if (!wo_ok && __all_sync(0xffffffffu, mbar_test(bar_wo + 8 * min(lane, 2), 0))) wo_frag(); });

        TW(12);
        if (!wo_ok) {
            for (int i = 0; i < 3; i++) mbar_wait(bar_wo + 8 * i, 0);
            wo_frag();
        }
        cons_sync();
        TS(6);
        const uint32_t b00 = lds32(bACT), b01 = lds32(bACT + 16), b10 = lds32(bACT + 32), b11 = lds32(bACT + 48);
        unsigned* dst = g_wop + (size_t)cta * (DM * NB) + warp * 128 + lane * 4;
#pragma unroll
        for (int i = 0; i < 5; i++) {
            if (i < 4 || warp < 4) {
                float acc[4] = {0.f, 0.f, 0.f, 0.f};
                mma16816(acc, aw[i][0], b00, b01);
                mma16816(acc, aw[i][1], b10, b11);
                put_partial(dst + i * 1024, acc, tag2);
            }
        }
    }
    TS(17);
    TW(14);
    const int kq = warp & 3, tg = warp >> 2;
    uint32_t ag[3][9][4];
    uint2 cbv[9], sbv[9];
    load_row16<9>(g_mod + warp * 3456 + 4 * DM, lane, cbv);
    load_row16<9>(g_mod + warp * 3456 + 3 * DM, lane, sbv);
    if (cta < NRED) {
        uint4 rv[8];
        const unsigned* rp = red_ptr(g_wop, cta, warp, lane);
        red_issue(rp, rv);
        const float s = red_finish(rp, rv, tag2, sb, tid, 16);
        TS(19);
        if (tid < 64) {
            xin = bfr(xin + bfr(bf_lo(gab) * bfr(s)));
            const unsigned me = bf_bits(xin), other = __shfl_xor_sync(0xffffffffu, me, 16);
            if (lane < 16) stg_relaxed1(&g_x2[ob * (DM / 2) + (ocol >> 1)], (me | (other << 16)) + 1u);
        }
    }
    TW(17);
    unsigned cpk[9], spk[9];
    fix_row16<9>(g_mod + warp * 3456 + 4 * DM, lane, tag16, cbv);
    fix_row16<9>(g_mod + warp * 3456 + 3 * DM, lane, tag16, sbv);
#pragma unroll
    for (int i = 0; i < 9; i++) {
        cpk[i] = pack_bf2(1.0f + bf_hi(cbv[i].x), 1.0f + bf_hi(cbv[i].y));
        spk[i] = pack_hi(sbv[i].x, sbv[i].y);
    }
    {
#pragma unroll
        for (int i = 0; i < 3; i++) {
            mbar_wait(bar_gate + 8 * i, 0);
            mbar_wait(bar_full + 8 * ((2 * nend + i) & 7), ((2 * nend + i) >> 3) & 1);
        }
        TW(23);
#pragma unroll
        for (int i = 0; i < 9; i++) {
            const int r0 = 144 * kq + 16 * i;
            const int box = r0 / 192;
            const uint32_t base = cs ? (sb + SM_RING + ((2 * nend + box) & 7) * TILE) : (sb + SM_WB + box * 15360);
            const uint32_t ab = base + (r0 - 192 * box + kr) * 80 + tg * 48;
            ldsm4t(ab, ag[0][i]);
            ldsm4t(ab + 16, ag[1][i]);
        }
        TW(15);
    }
    TS(8);
    {
        int nl = nend;
        asm volatile("" : "+r"(nl));
#pragma unroll
        for (int i = 3; i < 6; i++) mbar_wait(bar_full + 8 * ((2 * nl + i) & 7), ((2 * nl + i) >> 3) & 1);
        TW(3);
    }
    {
        unsigned xw[9];
        const unsigned* xp = g_x2 + warp * (DM / 2) + lane;
#pragma unroll
        for (int i = 0; i < 9; i++) xw[i] = ldg_relaxed1(xp + 32 * i);
        unsigned spins = 0;
        while (true) {
            bool ok = true;
#pragma unroll
            for (int i = 0; i < 9; i++)
                if (xw[i] == 0u) { xw[i] = ldg_relaxed1(xp + 32 * i); ok = false; }
            if (ok) break;
            if (++spins > SPIN_LIMIT) TRAP_AT(__LINE__);
        }
        __syncwarp();
        TS(20);
        TW(18);
#pragma unroll
        for (int i = 0; i < 9; i++) xw[i] -= 1u;
        unsigned mean2; float rsd;
        ln_stats(xw, mean2, rsd);
#pragma unroll
        for (int i = 0; i < 9; i++)
            sts32(bufA + (warp * BUFA_PITCH + 2 * (lane + 32 * i)) * 2, ln_apply(xw[i], mean2, rsd, cpk[i], spk[i]));
    }
    if (tg == 0) {
        int nl = nend;
        asm volatile("" : "+r"(nl));
#pragma unroll
        for (int i = 0; i < 9; i++) {
            const int r0 = 144 * kq + 16 * i;
            const int box = r0 / 192;
            const uint32_t base = cs ? (sb + SM_RING + ((2 * nl + box) & 7) * TILE) : (sb + SM_WB + box * 15360);
            ldsm4t(base + (r0 - 192 * box + kr) * 80 + 32, ag[2][i]);
        }
    }
    TW(19);
    cons_sync();
    TS(9);
    const uint32_t gred = sb + SM_RING + ((2 * nend + 6) & 7) * TILE;
    {
        float acc[3][4];
#pragma unroll
        for (int j = 0; j < 3; j++) acc[j][0] = acc[j][1] = acc[j][2] = acc[j][3] = 0.f;
        int ll = lane;
        asm volatile("" : "+r"(ll));
        const uint32_t bA2 = bufA + ((ll >> 2) * BUFA_PITCH + 2 * (ll & 3)) * 2;
#pragma unroll
        for (int i = 0; i < 9; i++) {
            const uint32_t b0 = lds32(bA2 + (9 * kq + i) * 32), b1 = lds32(bA2 + (9 * kq + i) * 32 + 16);
            mma16816(acc[0], ag[0][i], b0, b1);
            mma16816(acc[1], ag[1][i], b0, b1);
            if (tg == 0) mma16816(acc[2], ag[2][i], b0, b1);
        }
        const uint32_t ga = gred + ((kq * 5 + tg * 3) * 32 + lane) * 16;
        sts128f(ga, acc[0][0], acc[0][1], acc[0][2], acc[0][3]);
        sts128f(ga + 512, acc[1][0], acc[1][1], acc[1][2], acc[1][3]);
        if (tg == 0) sts128f(ga + 1024, acc[2][0], acc[2][1], acc[2][2], acc[2][3]);
    }
    TW(20);
    uint32_t ad[5][3][4];
    {
        int nl = nend;
        asm volatile("" : "+r"(nl));
        uint32_t sl[6];
#pragma unroll
        for (int i = 3; i < 6; i++) sl[i] = sb + SM_RING + ((2 * nl + i) & 7) * TILE;
#pragma unroll
        for (int ks = 0; ks < 3; ks++) {
            const int r = min(16 * ks + kr, 35);
            const uint32_t off = r * 128 + ((((warp & 3) * 2 + cs) ^ (r & 7)) << 4);
#pragma unroll
            for (int i = 0; i < 5; i++) {
                if (i < 4 || warp < 4) {
                    const int cb0 = 2 * i, cb1 = 2 * i + 1;
                    const uint32_t bx = wsw ? (sl[3 + (cb1 / 3 > 2 ? 2 : cb1 / 3)] + (cb1 % 3) * 5120) : (sl[3 + cb0 / 3] + (cb0 % 3) * 5120);
                    ldsm4t(bx + off, ad[i][ks]);
                }
            }
        }
    }
    TW(21);
    cons_sync();
    if (tid < 160) {
        const uint32_t ga = gred + tid * 16;
        float4 v = lds128f(ga);
#pragma unroll
        for (int k = 1; k < 4; k++) { const float4 u = lds128f(ga + k * 2560); v.x += u.x; v.y += u.y; v.z += u.z; v.w += u.w; }
        const int cl = 8 * warp + g - 4 * (cta & 1);
#pragma unroll
        for (int e = 0; e < 2; e++) {
            const float gt = bfr(e ? v.y : v.x), up = bfr(e ? v.w : v.z);
            const float inner = 0.7978845608028654f * fmaf(0.044715f * gt * gt, gt, gt);
            const float ge = bfr(gt * rcp(1.0f + ex2(inner * (-2.0f * LOG2E))));
            if (cl >= 0 && cl < 36) sts16(sb + SM_ACT + ((2 * t + e) * ACT_PITCH + cl) * 2, bf_bits(ge * up));
        }
    }
    TW(22);
    cons_sync();
    TS(10);
    {
        uint32_t b[3][2];
#pragma unroll
        for (int ks = 0; ks < 3; ks++) { b[ks][0] = lds32(bACT + ks * 32); b[ks][1] = lds32(bACT + ks * 32 + 16); }
        unsigned* dst = g_dnp + (size_t)cta * (DM * NB) + warp * 128 + lane * 4;
#pragma unroll
        for (int i = 0; i < 5; i++) {
            if (i < 4 || warp < 4) {
                float acc[4] = {0.f, 0.f, 0.f, 0.f};
#pragma unroll
                for (int ks = 0; ks < 3; ks++) mma16816(acc, ad[i][ks], b[ks][0], b[ks][1]);
                put_partial(dst + i * 1024, acc, tag2);
            }
        }
    }
    TS(11);
    TW(24);
    if (cta < NRED) {
        uint4 rv[8];
        const unsigned* rp = red_ptr(g_dnp, cta, warp, lane);
        red_issue(rp, rv);
        const float s = red_finish(rp, rv, tag2, sb, tid, 25);
        if (tid < 64) prm.out[ob * DM + ocol] = __float2bfloat16_rn(xin + bfr(bf_hi(gab) * bfr(s)));
    }
    TS(12);
    TW(26);
}

typedef CUresult (*EncodeFn)(CUtensorMap*, CUtensorMapDataType, cuuint32_t, void*, const cuuint64_t*, const cuuint64_t*,
                             const cuuint32_t*, const cuuint32_t*, CUtensorMapInterleave, CUtensorMapSwizzle,
                             CUtensorMapL2promotion, CUtensorMapFloatOOBfill);

bool make_map(EncodeFn fn, CUtensorMap* m, const void* ptr, uint64_t inner, uint64_t outer, uint64_t stride_bytes,
              uint32_t box_inner, uint32_t box_outer, CUtensorMapSwizzle sw, CUtensorMapL2promotion promo) {
    cuuint64_t dims[2] = {inner, outer};
    cuuint64_t strides[1] = {stride_bytes};
    cuuint32_t box[2] = {box_inner, box_outer};
    cuuint32_t es[2] = {1, 1};
    return fn(m, CU_TENSOR_MAP_DATA_TYPE_BFLOAT16, 2, const_cast<void*>(ptr), dims, strides, box, es,
              CU_TENSOR_MAP_INTERLEAVE_NONE, sw, promo, CU_TENSOR_MAP_FLOAT_OOB_FILL_NONE) == CUDA_SUCCESS;
}

}

extern "C" void kernel_launch(void* const* d_in, const int* in_sizes, int n_in, void* d_out, int out_size) {
    (void)in_sizes; (void)n_in; (void)out_size;
    static EncodeFn encode = nullptr;
    static int num_sms = 0;
    if (!encode) {
        void* fn = nullptr;
        cudaDriverEntryPointQueryResult qres;
        cudaGetDriverEntryPoint("cuTensorMapEncodeTiled", &fn, cudaEnableDefault, &qres);
        encode = (EncodeFn)fn;
        int dev = 0;
        cudaGetDevice(&dev);
        cudaDeviceGetAttribute(&num_sms, cudaDevAttrMultiProcessorCount, dev);
        cudaFuncSetAttribute(fused_kernel, cudaFuncAttributeMaxDynamicSharedMemorySize, SMEM_BYTES);
    }
    CUtensorMap tmK, tmV, tmQ, tmO, tmG, tmU, tmD;
    const uint64_t kvrows = (uint64_t)NPAIR * SK * 2;
    make_map(encode, &tmK, d_in[1], 64, kvrows, 128, 64, 128, CU_TENSOR_MAP_SWIZZLE_128B, CU_TENSOR_MAP_L2_PROMOTION_L2_256B);
    make_map(encode, &tmV, d_in[2], 64, kvrows, 128, 64, 128, CU_TENSOR_MAP_SWIZZLE_128B, CU_TENSOR_MAP_L2_PROMOTION_L2_256B);
    make_map(encode, &tmQ, d_in[3], 4096, DM, 8192, 32, 192, CU_TENSOR_MAP_SWIZZLE_64B, CU_TENSOR_MAP_L2_PROMOTION_L2_128B);
#define WPROMO CU_TENSOR_MAP_L2_PROMOTION_L2_128B
    make_map(encode, &tmO, d_in[4], DM, 4096, DM * 2, 64, 16, CU_TENSOR_MAP_SWIZZLE_128B, WPROMO);
    make_map(encode, &tmG, d_in[6], FF, DM, FF * 2, 40, 192, CU_TENSOR_MAP_SWIZZLE_NONE, WPROMO);
    make_map(encode, &tmU, d_in[7], FF, DM, FF * 2, 40, 192, CU_TENSOR_MAP_SWIZZLE_NONE, WPROMO);
    make_map(encode, &tmD, d_in[8], DM, FF, DM * 2, 64, 36, CU_TENSOR_MAP_SWIZZLE_128B, WPROMO);
    Params prm;
    prm.x = (const __nv_bfloat16*)d_in[0];
    prm.c = (const __nv_bfloat16*)d_in[9];
    prm.wmod = (const __nv_bfloat16*)d_in[10];
    prm.out = (__nv_bfloat16*)d_out;
    int grid = num_sms < MAXCTA ? num_sms : MAXCTA;
    fused_kernel<<<grid, NTHREADS, SMEM_BYTES>>>(tmK, tmV, tmQ, tmO, tmG, tmU, tmD, prm);
}
```
